```python
import torch

def _softmax(x, axis=-1):
    return torch.softmax(x, dim=axis)
def _gelu(x):
    return torch.nn.functional.gelu(x, approximate="tanh")
def _silu(x):
    return torch.nn.functional.silu(x)
def _sigmoid(x):
    return torch.sigmoid(x)
def _layernorm(x, axis=-1, eps=1e-5):
    m = x.mean(dim=axis, keepdim=True)
    v = x.var(dim=axis, keepdim=True, unbiased=False)
    return (x - m) / torch.sqrt(v + eps)
def _scatter_add(tgt, idx, src, axis=0):
    return tgt.clone().index_add_(axis, idx, src)
def _segment_sum(src, seg, n):
    out = torch.zeros((n,) + src.shape[1:], dtype=src.dtype)
    return out.index_add_(0, seg, src)
def _pad(x, pw):
    flat = tuple(v for pair in reversed(pw) for v in pair)
    return torch.nn.functional.pad(x, flat)

kernel_name = 'concat_heads__mha_block_cached__mha_block_cached__near_ridge'

def setup_inputs():

    _w = (lambda a: (lambda t: t.to(torch.bfloat16) if t.is_floating_point() else t)(torch.as_tensor(a)))
    def _A_setup():
        B, Sq, D = 16, 144, 512
        H, Sk, Dh = 32, 512, 128
        return {
            "x": _w((lambda *s: torch.randn(*s, dtype=torch.bfloat16) * 0.8)(B, Sq, D)),
            "k_cache": _w((lambda *s: torch.randn(*s, dtype=torch.bfloat16) * 0.8)(B, H, Sk, Dh)),
            "v_cache": _w((lambda *s: torch.randn(*s, dtype=torch.bfloat16) * 0.05)(B, H, Sk, Dh)),
            "wq": _w((lambda *s: torch.randn(*s, dtype=torch.bfloat16) * 0.8)(D, H * Dh) * (D ** -0.5)),
            "wo": _w((lambda *s: torch.randn(*s, dtype=torch.bfloat16) * 0.05)(H * Dh, D) * ((H * Dh) ** -0.5)),
        }
    _A_in = _A_setup()

    def _B_setup():
        B, Sq, D = 16, 144, 512
        H, Sk, Dh = 32, 512, 128
        return {
            "x": _w((lambda *s: torch.randn(*s, dtype=torch.bfloat16) * 0.8)(B, Sq, D)),
            "k_cache": _w((lambda *s: torch.randn(*s, dtype=torch.bfloat16) * 0.8)(B, H, Sk, Dh)),
            "v_cache": _w((lambda *s: torch.randn(*s, dtype=torch.bfloat16) * 0.05)(B, H, Sk, Dh)),
            "wq": _w((lambda *s: torch.randn(*s, dtype=torch.bfloat16) * 0.8)(D, H * Dh) * (D ** -0.5)),
            "wo": _w((lambda *s: torch.randn(*s, dtype=torch.bfloat16) * 0.05)(H * Dh, D) * ((H * Dh) ** -0.5)),
        }
    _B_in = _B_setup()

    return {
        "A_x": _A_in["x"],
        "A_k_cache": _A_in["k_cache"],
        "A_v_cache": _A_in["v_cache"],
        "A_wq": _A_in["wq"],
        "A_wo": _A_in["wo"],
        "B_x": _B_in["x"],
        "B_k_cache": _B_in["k_cache"],
        "B_v_cache": _B_in["v_cache"],
        "B_wq": _B_in["wq"],
        "B_wo": _B_in["wo"],
    }

def reference(A_x, A_k_cache, A_v_cache, A_wq, A_wo, B_x, B_k_cache, B_v_cache, B_wq, B_wo):
    def _A_ref(x, k_cache, v_cache, wq, wo):
        B, Sq, D = x.shape
        H, Dh = 32, 128
        q = (lambda x, *d: x.permute(*d))((x @ wq).reshape(B, Sq, H, Dh), 0, 2, 1, 3)
        scores = torch.einsum("bhqd,bhkd->bhqk", q, k_cache) * (Dh ** -0.5)
        p = _softmax(scores, axis=-1)
        o = torch.einsum("bhqk,bhkd->bhqd", p, v_cache)
        return (lambda x, *d: x.permute(*d))(o, 0, 2, 1, 3).reshape(B, Sq, H * Dh) @ wo

    def _B_ref(x, k_cache, v_cache, wq, wo):
        B, Sq, D = x.shape
        H, Dh = 32, 128
        q = (lambda x, *d: x.permute(*d))((x @ wq).reshape(B, Sq, H, Dh), 0, 2, 1, 3)
        scores = torch.einsum("bhqd,bhkd->bhqk", q, k_cache) * (Dh ** -0.5)
        p = _softmax(scores, axis=-1)
        o = torch.einsum("bhqk,bhkd->bhqd", p, v_cache)
        return (lambda x, *d: x.permute(*d))(o, 0, 2, 1, 3).reshape(B, Sq, H * Dh) @ wo

    a = _A_ref(A_x, A_k_cache, A_v_cache, A_wq, A_wo)
    b = _B_ref(B_x, B_k_cache, B_v_cache, B_wq, B_wo)
    return torch.concatenate([a, b], axis=-1)
```

```cpp
#include <cuda_runtime.h>
#include <cuda.h>
#include <cuda_bf16.h>
#include <cuda_fp16.h>
#include <stdint.h>

#define CFG_NA 6
#define CFG_NB 5
#define CFG_OSLOTS 2
#define CFG_D 4
#define CFG_PF 4
#define CFG_PF0 6
#define CFG_RELEASE 0
#define CFG_ORDER 2
#define CFG_TLA 6
#define CFG_TLB 7
#define CFG_MC 1
#define CFG_ROT 0
#define CFG_PFN 6
#define CFG_PFL 12
#define CFG_PFLIST 0x765432ull
#define CFG_LEAD 0
#define CFG_S0 12
#define CFG_PFEF 0
#define CFG_LA 0
#define CFG_STAGGER 0
#define CFG_WPF 1
#define CFG_KA 3
#define CFG_KB 5
#define CFG_QB 2
#define CFG_LOCAL 1
#define DBG_NOSAFE 0
#define DBG_KVHOT 0
#define CFG_L16 0
#define CFG_CREG 232
#define CFG_PREG 40
#define DBG_NOFLUSH 0
#define DBG_NOOX 0
#define CFG_WEF 0
#define CFG_PROMO CU_TENSOR_MAP_L2_PROMOTION_L2_128B

namespace {

constexpr int NA = CFG_NA;
constexpr int NB = CFG_NB;
constexpr int OSLOTS = CFG_OSLOTS;
constexpr int OPD = CFG_D;
constexpr int SQ = 144;
constexpr uint32_t A_BYTES = 8192, B_BYTES = 18432;
constexpr uint32_t OFF_A = 0;
constexpr uint32_t OFF_B = 2 * NA * A_BYTES;
constexpr uint32_t OFF_Q = OFF_B + NB * B_BYTES;
constexpr uint32_t OFF_LPART = OFF_Q + 2 * B_BYTES;
constexpr uint32_t OFF_LINV = OFF_LPART;
constexpr uint32_t OFF_LSUM = OFF_LPART + 576;
constexpr uint32_t OFF_M = OFF_LSUM + 576;
constexpr uint32_t OFF_FAC = OFF_M + 2 * 576;
constexpr int NFAC = 4;
constexpr uint32_t OFF_INFO = OFF_LPART + 8 * 576;
constexpr uint32_t OFF_SEL = OFF_INFO + 16;
constexpr uint32_t OFF_BAR = OFF_SEL + 16;
constexpr uint32_t BAR_FULLA = OFF_BAR;
constexpr uint32_t BAR_EMPTYA = BAR_FULLA + 2 * NA * 8;
constexpr uint32_t BAR_FULLB = BAR_EMPTYA + 2 * NA * 8;
constexpr uint32_t BAR_EMPTYB = BAR_FULLB + NB * 8;
constexpr uint32_t BAR_PGATE = BAR_EMPTYB + NB * 8;
constexpr uint32_t BAR_PEER = BAR_PGATE + NB * 8;
constexpr uint32_t BAR_PSTG = BAR_PEER + NB * 8;
constexpr uint32_t BAR_QFULL = BAR_PSTG + 32;
constexpr uint32_t BAR_QFREE = BAR_QFULL + 8;
constexpr uint32_t BAR_OSTG = BAR_QFREE + 16;
constexpr uint32_t BAR_LFULL = BAR_OSTG + 16;
constexpr uint32_t BAR_LREADY = BAR_LFULL + 8;
constexpr uint32_t BAR_REDO = BAR_LREADY + 8;
constexpr uint32_t OFF_TRACE = BAR_REDO + 8;
constexpr uint32_t SMEM_USED = OFF_TRACE;
constexpr uint32_t SMEM_BYTES = 232448;
static_assert(SMEM_USED <= SMEM_BYTES, "shared memory budget");
static_assert(OPD >= 1 && OPD <= 7 && NB >= 5 && OSLOTS == 2, "schedule");
constexpr int R1 = OPD <= 3 ? 1 : 2;
constexpr int NWIN = 2 * OSLOTS;

constexpr float SCL = 0.08838834764831845f * 1.4426950408889634f;
constexpr float L_MAX = 1099511627776.f;
constexpr float M_INIT = -3.0e38f;

struct Maps {
  CUtensorMap x[2], wq[2], k[2], v[2], wo[2], o, out;
};

__device__ uint4 g_scr[(128 * NWIN + 1) * 4096];
__device__ float4 g_acc[128 * 18 * 256];
__device__ unsigned long long g_flag[128 * 16];

#define TRACE(id)
#define TRACE_P(id)
#define TRACE_R(r)

__device__ __forceinline__ void mbar_init(uint32_t bar, uint32_t cnt) {
  asm volatile("mbarrier.init.shared::cta.b64 [%0], %1;" ::"r"(bar), "r"(cnt));
}
__device__ __forceinline__ void mbar_expect_tx(uint32_t bar, uint32_t bytes) {
  asm volatile("mbarrier.arrive.expect_tx.shared::cta.b64 _, [%0], %1;" ::"r"(bar), "r"(bytes) : "memory");
}
__device__ __forceinline__ void mbar_arrive(uint32_t bar) {
  asm volatile("mbarrier.arrive.shared::cta.b64 _, [%0];" ::"r"(bar) : "memory");
}
__device__ __forceinline__ void mbar_arrive_if(uint32_t bar, uint32_t pred) {
  asm volatile("{\n.reg .pred p;\nsetp.ne.u32 p, %1, 0;\n@p mbarrier.arrive.shared::cta.b64 _, [%0];\n}" ::"r"(bar), "r"(pred) : "memory");
}
__device__ __forceinline__ void mbar_wait(uint32_t bar, uint32_t parity) {
  asm volatile(
      "{\n.reg .pred p, q;\n.reg .u32 c;\n"
      "mov.u32 c, 0;\n"
      "WL:\n"
      "mbarrier.try_wait.parity.shared::cta.b64 p, [%0], %1;\n"
      "@p bra WD;\n"
      "add.u32 c, c, 1;\n"
      "setp.lt.u32 q, c, 4194304;\n"
      "@q bra WL;\n"
      "trap;\n"
      "WD:\n}" ::"r"(bar), "r"(parity) : "memory");
}
__device__ __forceinline__ void mbar_wait2(uint32_t b0, uint32_t p0, uint32_t b1, uint32_t p1) {
  asm volatile(
      "{\n.reg .pred p, q;\n.reg .u32 c;\n"
      "mov.u32 c, 0;\n"
      "WL:\n"
      "mbarrier.try_wait.parity.shared::cta.b64 p, [%0], %1;\n"
      "mbarrier.try_wait.parity.shared::cta.b64 q, [%2], %3;\n"
      "and.pred p, p, q;\n"
      "@p bra WD;\n"
      "add.u32 c, c, 1;\n"
      "setp.lt.u32 q, c, 4194304;\n"
      "@q bra WL;\n"
      "trap;\n"
      "WD:\n}" ::"r"(b0), "r"(p0), "r"(b1), "r"(p1) : "memory");
}
__device__ __forceinline__ uint32_t mbar_test(uint32_t bar, uint32_t parity) {
  uint32_t ok;
  asm volatile("{\n.reg .pred p;\nmbarrier.test_wait.parity.shared::cta.b64 p, [%1], %2;\nselp.u32 %0, 1, 0, p;\n}"
               : "=r"(ok) : "r"(bar), "r"(parity) : "memory");
  return ok;
}
__device__ __forceinline__ void tma_put2(uint32_t dst, const CUtensorMap* map, int c0, int c1, uint32_t bar, uint32_t bytes, uint64_t pol) {
  asm volatile(
      "{\n.reg .pred p;\nelect.sync _|p, 0xffffffff;\n"
      "@p mbarrier.arrive.expect_tx.shared::cta.b64 _, [%2], %5;\n"
      "@p cp.async.bulk.tensor.2d.shared::cluster.global.mbarrier::complete_tx::bytes.L2::cache_hint [%0], [%1, {%3, %4}], [%2], %6;\n}"
      ::"r"(dst), "l"(map), "r"(bar), "r"(c0), "r"(c1), "r"(bytes), "l"(pol) : "memory");
}
__device__ __forceinline__ void tma_put3(uint32_t dst, const CUtensorMap* map, int c1, int c2, uint32_t bar, uint32_t bytes) {
  asm volatile(
      "{\n.reg .pred p;\nelect.sync _|p, 0xffffffff;\n"
      "@p mbarrier.arrive.expect_tx.shared::cta.b64 _, [%2], %5;\n"
      "@p cp.async.bulk.tensor.3d.shared::cluster.global.mbarrier::complete_tx::bytes [%0], [%1, {0, %3, %4}], [%2];\n}"
      ::"r"(dst), "l"(map), "r"(bar), "r"(c1), "r"(c2), "r"(bytes) : "memory");
}
__device__ __forceinline__ void expect_elect(uint32_t bar, uint32_t bytes) {
  asm volatile("{\n.reg .pred p;\nelect.sync _|p, 0xffffffff;\n@p mbarrier.arrive.expect_tx.shared::cta.b64 _, [%0], %1;\n}" ::"r"(bar), "r"(bytes) : "memory");
}
__device__ __forceinline__ void arrive_remote_elect(uint32_t bar, uint32_t rank) {
  asm volatile("{\n.reg .pred p;\n.reg .b32 ra;\nelect.sync _|p, 0xffffffff;\nmapa.shared::cluster.u32 ra, %0, %1;\n"
               "@p mbarrier.arrive.shared::cluster.b64 _, [ra];\n}" ::"r"(bar), "r"(rank) : "memory");
}
__device__ __forceinline__ void tma_mc2(uint32_t dst, const CUtensorMap* map, int c0, int c1, uint32_t bar) {
  asm volatile("{\n.reg .pred p;\nelect.sync _|p, 0xffffffff;\n"
               "@p cp.async.bulk.tensor.2d.shared::cluster.global.mbarrier::complete_tx::bytes.multicast::cluster [%0], [%1, {%3, %4}], [%2], %5;\n}"
               ::"r"(dst), "l"(map), "r"(bar), "r"(c0), "r"(c1), "h"((uint16_t)3) : "memory");
}
__device__ __forceinline__ void tma_mc3(uint32_t dst, const CUtensorMap* map, int c1, int c2, uint32_t bar) {
  asm volatile("{\n.reg .pred p;\nelect.sync _|p, 0xffffffff;\n"
               "@p cp.async.bulk.tensor.3d.shared::cluster.global.mbarrier::complete_tx::bytes.multicast::cluster [%0], [%1, {0, %3, %4}], [%2], %5;\n}"
               ::"r"(dst), "l"(map), "r"(bar), "r"(c1), "r"(c2), "h"((uint16_t)3) : "memory");
}
__device__ __forceinline__ void bulk_prefetch_elect(const void* p, uint32_t bytes) {
  asm volatile("{\n.reg .pred p;\nelect.sync _|p, 0xffffffff;\n@p cp.async.bulk.prefetch.L2.global [%0], %1;\n}" ::"l"(p), "r"(bytes) : "memory");
}
__device__ __forceinline__ void tma_store3(const CUtensorMap* map, int c1, int c2, uint32_t src) {
  asm volatile("cp.async.bulk.tensor.3d.global.shared::cta.bulk_group [%0, {0, %2, %3}], [%1];"
               ::"l"(map), "r"(src), "r"(c1), "r"(c2) : "memory");
}
__device__ __forceinline__ uint32_t probe_window(char* win) {
  uint32_t votes = 0;
#pragma unroll 1
  for (int i = 0; i < 3; i++) {
    uint32_t t0, t1, v0, v1;
    asm volatile("atom.relaxed.gpu.global.exch.b32 %0, [%2], %3;\n\tatom.relaxed.gpu.global.exch.b32 %1, [%2+8192], %3;"
                 : "=r"(v0), "=r"(v1) : "l"(win + 53248), "r"(i) : "memory");
    asm volatile("{\n.reg .pred p;\nsetp.eq.u32 p, %1, 0xffffffff;\n@p mov.u32 %0, 0;\n@!p mov.u32 %0, %%clock;\n}" : "=r"(t0) : "r"(v0) : "memory");
    asm volatile("{\n.reg .pred p;\nsetp.eq.u32 p, %1, 0xffffffff;\n@p mov.u32 %0, 0;\n@!p mov.u32 %0, %%clock;\n}" : "=r"(t1) : "r"(v1) : "memory");
    votes += t1 - t0 < 90;
  }
  return CFG_LOCAL == 2 ? votes < 2 : (CFG_LOCAL ? votes >= 2 : 0);
}
__device__ __forceinline__ void tma_load(uint32_t dst, const CUtensorMap* map, int c0, int c1, uint32_t bar) {
  asm volatile("cp.async.bulk.tensor.2d.shared::cluster.global.mbarrier::complete_tx::bytes [%0], [%1, {%3, %4}], [%2];"
               ::"r"(dst), "l"(map), "r"(bar), "r"(c0), "r"(c1) : "memory");
}
__device__ __forceinline__ void tma_load_hint(uint32_t dst, const CUtensorMap* map, int c0, int c1, uint32_t bar, uint64_t pol) {
  asm volatile("cp.async.bulk.tensor.2d.shared::cluster.global.mbarrier::complete_tx::bytes.L2::cache_hint [%0], [%1, {%3, %4}], [%2], %5;"
               ::"r"(dst), "l"(map), "r"(bar), "r"(c0), "r"(c1), "l"(pol) : "memory");
}
__device__ __forceinline__ void tma_store(const CUtensorMap* map, int c0, int c1, uint32_t src) {
  asm volatile("cp.async.bulk.tensor.2d.global.shared::cta.bulk_group [%0, {%2, %3}], [%1];"
               ::"l"(map), "r"(src), "r"(c0), "r"(c1) : "memory");
}
__device__ __forceinline__ void bulk_prefetch(const void* p, uint32_t bytes) {
  asm volatile("cp.async.bulk.prefetch.L2.global [%0], %1;" ::"l"(p), "r"(bytes) : "memory");
}
__device__ __forceinline__ void prefetch_l2(const void* p) { asm volatile("prefetch.global.L2 [%0];" ::"l"(p)); }
__device__ __forceinline__ void fence_async_smem() { asm volatile("fence.proxy.async.shared::cta;" ::: "memory"); }
__device__ __forceinline__ void fence_async_global() { asm volatile("fence.proxy.async.global;" ::: "memory"); }
__device__ __forceinline__ void wg_fence() { asm volatile("wgmma.fence.sync.aligned;" ::: "memory"); }
__device__ __forceinline__ void wg_commit() { asm volatile("wgmma.commit_group.sync.aligned;" ::: "memory"); }
template <int N> __device__ __forceinline__ void wg_wait() { asm volatile("wgmma.wait_group.sync.aligned %0;" ::"n"(N) : "memory"); }
__device__ __forceinline__ void pin(float (&d)[72]) {
#pragma unroll
  for (int i = 0; i < 72; i++) asm volatile("" : "+f"(d[i])::"memory");
}
__device__ __forceinline__ void bar_sync(uint32_t id) { asm volatile("bar.sync %0, 128;" ::"r"(id) : "memory"); }
__device__ __forceinline__ float ex2(float x) { float y; asm("ex2.approx.ftz.f32 %0, %1;" : "=f"(y) : "f"(x)); return y; }
__device__ __forceinline__ float rcp(float x) { float y; asm("rcp.approx.f32 %0, %1;" : "=f"(y) : "f"(x)); return y; }
__device__ __forceinline__ uint32_t pack_bf16(float lo, float hi) {
  uint32_t r; asm("cvt.rn.bf16x2.f32 %0, %1, %2;" : "=r"(r) : "f"(hi), "f"(lo)); return r;
}
__device__ __forceinline__ void stsm_t(uint32_t addr, uint32_t r0, uint32_t r1, uint32_t r2, uint32_t r3) {
  asm volatile("stmatrix.sync.aligned.m8n8.x4.trans.shared.b16 [%0], {%1, %2, %3, %4};"
               ::"r"(addr), "r"(r0), "r"(r1), "r"(r2), "r"(r3) : "memory");
}
__device__ __forceinline__ float4 lds128(uint32_t a) {
  float4 v; asm volatile("ld.shared.v4.f32 {%0, %1, %2, %3}, [%4];" : "=f"(v.x), "=f"(v.y), "=f"(v.z), "=f"(v.w) : "r"(a) : "memory"); return v;
}
__device__ __forceinline__ float2 lds64(uint32_t a) {
  float2 v; asm volatile("ld.shared.v2.f32 {%0, %1}, [%2];" : "=f"(v.x), "=f"(v.y) : "r"(a) : "memory"); return v;
}
__device__ __forceinline__ float lds32(uint32_t a) { float v; asm volatile("ld.shared.f32 %0, [%1];" : "=f"(v) : "r"(a) : "memory"); return v; }
__device__ __forceinline__ uint32_t lds32u(uint32_t a) { uint32_t v; asm volatile("ld.shared.u32 %0, [%1];" : "=r"(v) : "r"(a) : "memory"); return v; }
__device__ __forceinline__ void sts32(uint32_t a, float v) { asm volatile("st.shared.f32 [%0], %1;" ::"r"(a), "f"(v) : "memory"); }
__device__ __forceinline__ void sts32u(uint32_t a, uint32_t v) { asm volatile("st.shared.u32 [%0], %1;" ::"r"(a), "r"(v) : "memory"); }
template <int TA>
__device__ __forceinline__ void wgmma_n144(float (&d)[72], uint32_t da, uint32_t db, uint32_t scale_d) {
  asm volatile("{\n.reg .pred p;\n.reg .b64 da, db;\nsetp.ne.b32 p, %74, 0;\n"
    "mov.b64 da, {%72, %76};\nmov.b64 db, {%73, %76};\n"
    "wgmma.mma_async.sync.aligned.m64n144k16.f32.bf16.bf16 "
    "{%0, %1, %2, %3, %4, %5, %6, %7, %8, %9, %10, %11, %12, %13, %14, %15, %16, %17, "
    "%18, %19, %20, %21, %22, %23, %24, %25, %26, %27, %28, %29, %30, %31, %32, %33, %34, %35, "
    "%36, %37, %38, %39, %40, %41, %42, %43, %44, %45, %46, %47, %48, %49, %50, %51, %52, %53, "
    "%54, %55, %56, %57, %58, %59, %60, %61, %62, %63, %64, %65, %66, %67, %68, %69, %70, %71}, "
    "da, db, p, 1, 1, %75, 0;\n}\n"
    : "+f"(d[0]), "+f"(d[1]), "+f"(d[2]), "+f"(d[3]), "+f"(d[4]), "+f"(d[5]), "+f"(d[6]), "+f"(d[7]),
      "+f"(d[8]), "+f"(d[9]), "+f"(d[10]), "+f"(d[11]), "+f"(d[12]), "+f"(d[13]), "+f"(d[14]), "+f"(d[15]),
      "+f"(d[16]), "+f"(d[17]), "+f"(d[18]), "+f"(d[19]), "+f"(d[20]), "+f"(d[21]), "+f"(d[22]), "+f"(d[23]),
      "+f"(d[24]), "+f"(d[25]), "+f"(d[26]), "+f"(d[27]), "+f"(d[28]), "+f"(d[29]), "+f"(d[30]), "+f"(d[31]),
      "+f"(d[32]), "+f"(d[33]), "+f"(d[34]), "+f"(d[35]), "+f"(d[36]), "+f"(d[37]), "+f"(d[38]), "+f"(d[39]),
      "+f"(d[40]), "+f"(d[41]), "+f"(d[42]), "+f"(d[43]), "+f"(d[44]), "+f"(d[45]), "+f"(d[46]), "+f"(d[47]),
      "+f"(d[48]), "+f"(d[49]), "+f"(d[50]), "+f"(d[51]), "+f"(d[52]), "+f"(d[53]), "+f"(d[54]), "+f"(d[55]),
      "+f"(d[56]), "+f"(d[57]), "+f"(d[58]), "+f"(d[59]), "+f"(d[60]), "+f"(d[61]), "+f"(d[62]), "+f"(d[63]),
      "+f"(d[64]), "+f"(d[65]), "+f"(d[66]), "+f"(d[67]), "+f"(d[68]), "+f"(d[69]), "+f"(d[70]), "+f"(d[71])
    : "r"(da), "r"(db), "r"(scale_d), "n"(TA), "r"(0x40000040));
}
__device__ __forceinline__ uint32_t desc_lo(uint32_t addr) { return (addr >> 4) | 0x10000u; }
template <int TA>
__device__ __forceinline__ void mma_tile(float (&acc)[72], uint32_t da, uint32_t db, uint32_t keep) {
#pragma unroll
  for (int k = 0; k < 4; k++) wgmma_n144<TA>(acc, da + (TA ? 128 : 2) * k, db + 2 * k, k == 0 ? keep : 1u);
}

template <int N> struct Cursor {
  uint32_t slot = 0, ph = 0;
  __device__ __forceinline__ void next() { if (++slot == N) { slot = 0; ph ^= 1; } }
  __device__ __forceinline__ void skip(uint32_t k) { const uint32_t t = slot + k, q = t / N; slot = t - q * N; ph ^= q & 1; }
};

template <bool MAX> __device__ __forceinline__ float comb(float a, float b) { return MAX ? fmaxf(a, b) : a + b; }
template <bool MAX> __device__ __forceinline__ float xsplit(float lo, float hi, bool bit, int mask) {
  const float send = bit ? lo : hi, keep = bit ? hi : lo;
  return comb<MAX>(keep, __shfl_xor_sync(0xffffffffu, send, mask));
}
template <bool MAX> __device__ __forceinline__ void col_reduce(const float (&v)[36], float (&o)[5], int lane) {
  const bool b2 = lane & 16, b1 = lane & 8, b0 = lane & 4;
#pragma unroll
  for (int G = 0; G < 5; G++) {
    float a[4];
#pragma unroll
    for (int e = 0; e < 4; e++) a[e] = G < 4 ? xsplit<MAX>(v[8 * G + e], v[(8 * G + 4 + e) % 36], b2, 16) : v[8 * G + e];
    const float c0 = xsplit<MAX>(a[0], a[2], b1, 8), c1 = xsplit<MAX>(a[1], a[3], b1, 8);
    float r = xsplit<MAX>(c0, c1, b0, 4);
    if (G == 4) r = comb<MAX>(r, __shfl_xor_sync(0xffffffffu, r, 16));
    o[G] = r;
  }
}

__device__ __forceinline__ int n_op(int r) { return (r < R1 || r == 8) ? 0 : (r == R1 ? 8 * R1 - OPD : 8); }

struct Consumer {
  uint32_t sb;
  uint32_t abar, adesc;
  uint32_t lane0;
  Cursor<NA> ac, ar;
  Cursor<NB> bc, br;

  __device__ __forceinline__ void rel_a(uint32_t on = 1) {
    mbar_arrive_if(abar + 2 * NA * 8 + ar.slot * 8, lane0 & on);
    if (on) ar.next();
  }
  __device__ __forceinline__ void rel_ab(uint32_t on = 1) {
    rel_a(on);
    mbar_arrive_if(sb + BAR_EMPTYB + br.slot * 8, lane0 & on);
    if (on) br.next();
  }
  uint32_t rdy = 0;
  __device__ __forceinline__ void test_next() { rdy = mbar_test(abar + ac.slot * 8, ac.ph) & mbar_test(sb + BAR_FULLB + bc.slot * 8, bc.ph); }
  __device__ __forceinline__ void step(float (&acc)[72], uint32_t keep) {
    const uint32_t da = adesc + ac.slot * (A_BYTES >> 4), db = desc_lo(sb + OFF_B) + bc.slot * (B_BYTES >> 4);
    if (!rdy) mbar_wait2(abar + ac.slot * 8, ac.ph, sb + BAR_FULLB + bc.slot * 8, bc.ph);
    ac.next();
    bc.next();
    wg_fence();
    test_next();
    mma_tile<1>(acc, da, db, keep);
    wg_commit();
  }
  __device__ __forceinline__ uint32_t test_s() {
    Cursor<NA> n = ac;
    n.next();
    return mbar_test(abar + ac.slot * 8, ac.ph) & mbar_test(abar + n.slot * 8, n.ph);
  }
  __device__ __forceinline__ void step_s(float (&acc)[72], uint32_t ready) {
    const uint32_t d0 = adesc + ac.slot * (A_BYTES >> 4), b0 = abar + ac.slot * 8, p0 = ac.ph;
    ac.next();
    const uint32_t d1 = adesc + ac.slot * (A_BYTES >> 4);
    if (!ready) mbar_wait2(b0, p0, abar + ac.slot * 8, ac.ph);
    ac.next();
    wg_fence();
    mma_tile<0>(acc, d0, desc_lo(sb + OFF_Q), 0);
    test_next();
    mma_tile<0>(acc, d1, desc_lo(sb + OFF_Q + B_BYTES), 1);
    wg_commit();
  }
};

template <uint32_t V> struct Const { static constexpr uint32_t value = V; };

struct Ptrs {
  const char *k[2], *v[2], *wq[2], *wo[2];
  char* scr;
};

__global__ void __launch_bounds__(384, 1)
fused_mha_kernel(const __grid_constant__ Maps maps, const __grid_constant__ Ptrs ptrs) {
  extern __shared__ __align__(1024) uint8_t smem_raw[];
  const uint32_t sb = (uint32_t)__cvta_generic_to_shared(smem_raw);
  const int tid = threadIdx.x;
  const int warp = __shfl_sync(0xffffffffu, tid >> 5, 0);
  const int lane = tid & 31;
  int cta = blockIdx.x;
  if (CFG_MC) {
    const int k = cta >> 1;
    int gpc = 0, row = k;
    if (k >= 36) { row = 4 + (k - 36) / 7; gpc = 1 + (k - 36) % 7; }
    else if (k >= 4) { gpc = (k - 4) & 7; row = ((k - 4) >> 3) + (gpc ? 0 : 4); }
    cta = gpc * 16 + row * 2 + (cta & 1);
  }
  const int c = cta & 3, grp = cta >> 2, br = grp >> 4, b = grp & 15;

  if (lane == 0) {
#pragma unroll 1
    for (uint32_t a = OFF_BAR + warp * 8; a < OFF_TRACE; a += 96) {
      uint32_t cnt = 1;
      if ((a >= BAR_EMPTYA && a < BAR_FULLB) || (a >= BAR_PSTG && a < BAR_QFULL)) cnt = 4;
      if ((a >= BAR_EMPTYB && a < BAR_PGATE) || a == BAR_QFULL || a == BAR_LFULL) cnt = 8;
      if (a == BAR_OSTG || a == BAR_OSTG + 8) cnt = 5;
      mbar_init(sb + a, cnt);
    }
    if (warp == 0) sts32u(sb + OFF_INFO + 4, 0);
    asm volatile("fence.mbarrier_init.release.cluster;" ::: "memory");
  }
  if (CFG_MC) asm volatile("barrier.cluster.arrive.release.aligned;\nbarrier.cluster.wait.acquire.aligned;" ::: "memory");
  else __syncthreads();

  if (warp >= 8) {
    asm volatile("setmaxnreg.dec.sync.aligned.u32 %0;" ::"n"(CFG_PREG));
    constexpr uint64_t POL_FIRST = DBG_KVHOT ? 0x1000000000000001ull - 1 : 0x12F0000000000000ull, POL_NORMAL = 0x1000000000000000ull;
    if (warp < 10) {
      const int x = warp - 8;
      const uint32_t bar0 = sb + BAR_FULLA + x * NA * 8, dst0 = sb + OFF_A + x * NA * A_BYTES;
      Cursor<NA> cur;
      unsigned t_begin;
      asm volatile("mov.u32 %0, %%clock;" : "=r"(t_begin));
      int item = 0, pfp = 0;
      auto put = [&](const CUtensorMap* m, int c0, int c1, uint64_t pol) {
        mbar_wait(bar0 + 2 * NA * 8 + cur.slot * 8, cur.ph ^ 1);
        if (lane == 0) TRACE_P(pol == POL_FIRST ? 31 : 30);
        tma_put2(dst0 + cur.slot * A_BYTES, m, c0, c1, bar0 + cur.slot * 8, A_BYTES, pol);
        cur.next();
        if (CFG_PFN && x == 1) {
          const int p = ++item + CFG_LEAD;
          int tg = CFG_PFN * (p >> 5) + min(CFG_PFN, ((p & 31) * CFG_PFN + CFG_PFL - 1) / CFG_PFL);
          if (item < 32) tg = item <= CFG_PF0 ? 0 : max(tg, CFG_PFN);
          for (; pfp < tg && pfp < 8 * CFG_PFN; pfp++) {
            const int q = (int)(CFG_PFLIST >> (4 * (pfp % (CFG_PFN ? CFG_PFN : 1)))) & 15;
            bulk_prefetch_elect((q & 8 ? ptrs.v[br] : ptrs.k[br]) + (size_t)(b * 32 + c + 4 * (pfp / (CFG_PFN ? CFG_PFN : 1))) * 131072 + (q & 7) * 16384, 16384);
          }
        }
      };
      constexpr uint64_t POL_W = CFG_WEF ? POL_FIRST : POL_NORMAL;
#pragma unroll 1
      for (int pass = 0; pass < 2; pass++) {
        int g = 0;
        auto wo_row = [&]() { return (g >> 3) * 512 + (((c & CFG_ROT) * 128 + (g & 7) * 64) & 511); };
#pragma unroll 1
        for (int r = 0; r <= 8; r++) {
          TRACE_R(r);
          const int n = n_op(r);
          item = 32 * r;
          if (r < 8) {
#pragma unroll 1
            for (int i = 0; i < 8; i++) put(&maps.wq[br], (4 * r + c) * 128 + 64 * x, 64 * i, POL_W);
          }
#pragma unroll 1
          for (int i = r < 8 ? (n ? n - 4 + 2 * x : 0) : 8 + OPD; i > 0; i--, g++) put(&maps.wo[br], 128 * c + 64 * x, wo_row(), POL_W);
          if (r == 8) break;
          item = 32 * r + 12 + 2 * x;
          if (CFG_STAGGER && r == 0 && br) {
            unsigned t_;
            for (;;) { asm volatile("mov.u32 %0, %%clock;" : "=r"(t_)); if (t_ - t_begin >= CFG_STAGGER) break; __nanosleep(100); }
          }
          const int kv = DBG_KVHOT == 1 ? ((b & 1) * 32 + c) * 512 : (DBG_KVHOT == 2 ? ((b >> 1) * 32 + c) * 512 : (b * 32 + 4 * r + c) * 512);
          int vrow = kv;
#pragma unroll 1
          for (int j = 0; j < 4; j++) {
#pragma unroll 1
            for (int h = 0; h < 2; h++) put(&maps.k[br], 64 * h, kv + 64 * (2 * j + x), POL_FIRST);
            if (j + x < 2) {
#pragma unroll 1
              for (int h = n ? 2 : 0; h > 0; h--, g++) put(&maps.wo[br], 128 * c + 64 * x, wo_row(), POL_W);
            } else {
#pragma unroll 1
              for (int h = j < 3 ? 2 : 6 - 2 * x; h > 0; h--, vrow += 64) put(&maps.v[br], 64 * x, vrow, POL_FIRST);
            }
          }
        }
        if (pass) break;
        mbar_wait(sb + BAR_REDO, 0);
        if (!__shfl_sync(0xffffffffu, lds32u(sb + OFF_INFO + 8), 0)) break;
      }
    } else if (warp == 10) {
      const unsigned base = (unsigned)*(volatile unsigned long long*)&g_flag[cta * 16];
      const unsigned long long* const fp = &g_flag[(grp * 4 + (lane & 3)) * 16];
      uint32_t pubs = 0, sels = 0;
      Cursor<NB> cur;
      uint32_t gate = NB, gph = 1;
      auto poll = [&]() {
        unsigned long long fv;
        asm volatile("ld.acquire.gpu.global.u64 %0, [%1];" : "=l"(fv) : "l"(fp) : "memory");
        pubs = __reduce_or_sync(0xffffffffu, (((unsigned)fv - base) & 255) << (8 * (lane & 3)));
        sels = __reduce_or_sync(0xffffffffu, ((uint32_t)(fv >> 32) & 255) << (8 * (lane & 3)));
        __syncwarp();
        fence_async_global();
        if (lane == 0) TRACE_P(33);
      };
      auto need = [&](int hh, uint32_t rounds) {
        for (int spin = 0; ((pubs >> (8 * hh)) & 255) < 2 * rounds; spin++) {
          if (spin) __nanosleep(20);
          if (spin > (1 << 23)) asm volatile("trap;");
          poll();
        }
      };
      auto war_gate = [&](uint32_t rounds) {
        for (int spin = 0;; spin++) {
          unsigned v;
          asm volatile("ld.relaxed.gpu.global.u32 %0, [%1];" : "=r"(v) : "l"(fp + 1) : "memory");
          poll();
          if (__all_sync(0xffffffffu, (int)(v - base - rounds) >= 0)) break;
          if (spin > (1 << 23)) asm volatile("trap;");
          __nanosleep(20);
        }
        mbar_arrive_if(sb + BAR_OSTG + (lane & 1) * 8, lane < 2);
      };
      auto slot_wait = [&]() {
        if (gate < NB) mbar_wait(sb + BAR_PGATE + 8 * gate, gph);
        gate++;
        mbar_wait(sb + BAR_EMPTYB + cur.slot * 8, cur.ph ^ 1);
        if (lane == 0) TRACE_P(32);
      };
      uint32_t peer_ph = 0;
      auto mine = [&](int i) {
        expect_elect(sb + BAR_FULLB + cur.slot * 8, B_BYTES);
        if ((i ^ c) & 1) {
          arrive_remote_elect(sb + BAR_PEER + cur.slot * 8, (c & 1) ^ 1);
          return false;
        }
        mbar_wait(sb + BAR_PEER + cur.slot * 8, (peer_ph >> cur.slot) & 1);
        peer_ph ^= 1u << cur.slot;
        return true;
      };
#pragma unroll 1
      for (int pass = 0; pass < 2; pass++) {
        int g = 0;
#pragma unroll 1
        for (int r = 0; r <= 8; r++) {
          TRACE_R(r);
#pragma unroll 1
          for (int i = r < 8 ? 0 : 8; i < 8; i++) {
            if (i == 2 && r > 0) war_gate(pass * 8 + r);
            slot_wait();
            const uint32_t dst = sb + OFF_B + cur.slot * B_BYTES, fb = sb + BAR_FULLB + cur.slot * 8;
            if (!CFG_MC) tma_put2(dst, &maps.x[br], 64 * i, b * SQ, fb, B_BYTES, POL_NORMAL);
            else if (mine(i)) tma_mc2(dst, &maps.x[br], 64 * i, b * SQ, fb);
            cur.next();
          }
#pragma unroll 1
          for (int i = r < 8 ? n_op(r) : 8 + OPD; i > 0; i--, g++) {
            const int hh = ((c & CFG_ROT) + (g >> 1)) & 3, ro = pass * 8 + (g >> 3), w = 2 * (ro % OSLOTS) + (g & 1);
            if (!CFG_MC || ((g ^ c) & 1) == 0) need(hh, ro + 1);
            slot_wait();
            const uint32_t dst = sb + OFF_B + cur.slot * B_BYTES, fb = sb + BAR_FULLB + cur.slot * 8;
            const int c1 = ((sels >> (8 * hh + w)) & 1) * 64, c2 = ((grp * 4 + hh) * NWIN + w) * 4;
            if (!CFG_MC) tma_put3(dst, &maps.o, c1, c2, fb, B_BYTES);
            else if (mine(g)) tma_mc3(dst, &maps.o, c1, c2, fb);
            cur.next();
          }
          if (__builtin_expect(r + pass == 0, 0)) {
            char* const scr = ptrs.scr + (size_t)cta * NWIN * 65536;
            uint32_t v, sel = 0;
            if (lane < 2 * NWIN) {
              asm volatile("atom.relaxed.gpu.global.exch.b32 %0, [%1], 0;" : "=r"(v) : "l"(scr + (lane >> 1) * 65536 + 53248 + (lane & 1) * 8192) : "memory");
              sel = v == 0xffffffffu;
            }
            sel = __reduce_and_sync(0xffffffffu, sel);
            if (lane == 0) {
#pragma unroll 1
              for (int w = 0; w < NWIN; w++) sel |= probe_window(scr + w * 65536) << w;
              sts32u(sb + OFF_SEL, sel);
            }
            __syncwarp();
          }
          if (r < 8) {
            cur.skip(8);
            gate = 0;
            gph ^= 1;
            mbar_wait(sb + BAR_PGATE, gph);
            if (lane == 0) asm volatile("st.relaxed.gpu.global.u32 [%0], %1;" ::"l"(&g_flag[cta * 16 + 1]), "r"(base + pass * 8 + r + 1) : "memory");
            if (r == 7) war_gate(pass * 8 + 8);
          } else {
            mbar_arrive_if(sb + BAR_OSTG + (lane & 1) * 8, lane < 2);
          }
        }
        if (pass) break;
        const uint32_t redo = pubs != 0x10101010u;
        if (lane == 0) {
          sts32u(sb + OFF_INFO + 8, redo);
          mbar_arrive(sb + BAR_REDO);
        }
        if (!redo) break;
      }
    } else {
      const unsigned base = (unsigned)*(volatile unsigned long long*)&g_flag[cta * 16];
      Cursor<NB> cur;
#pragma unroll 1
      for (int pass = 0; pass < 2; pass++) {
        unsigned bad = 0;
#pragma unroll 1
        for (int p = pass ? lane : SQ; p < SQ; p += 32) sts32(sb + OFF_LSUM + p * 4, 0.f);
        __syncwarp();
#pragma unroll 1
        for (int r = 0; r <= 8; r++) {
          TRACE_R(r);
          const int R = pass * 8 + r;
          cur.skip(r < 8 ? 8 + n_op(r) : 8 + OPD);
          if (r < 8) {
            if (CFG_WPF) {
              const char* wq = ptrs.wq[br] + (size_t)(b * 32 + lane) * 8192 + (4 * (r + 1) + c) * 256;
              const char* wo = ptrs.wo[br] + (size_t)(r * 512 + b * 32 + lane) * 1024 + c * 256;
              if (r < 7) { prefetch_l2(wq); prefetch_l2(wq + 128); }
              prefetch_l2(wo); prefetch_l2(wo + 128);
            }
#pragma unroll 1
            for (int t = 0; t < 8; t++) {
              mbar_wait(sb + BAR_PSTG + (t & 3) * 8, t >> 2);
              fence_async_smem();
              mbar_arrive_if(sb + BAR_FULLB + cur.slot * 8, lane == 0);
              mbar_arrive_if(sb + BAR_PGATE + (t - (8 - NB)) * 8, lane == 0 && t >= 8 - NB);
              if (lane == 0) TRACE_P(46);
              cur.next();
            }
            __syncwarp();
            mbar_wait(sb + BAR_LFULL, r & 1);
            if (__builtin_expect(pass, 0)) {
#pragma unroll 1
              for (int p = lane; p < SQ; p += 32) {
                sts32(sb + OFF_LINV + p * 4, rcp(lds32(sb + OFF_LSUM + p * 4)));
                sts32(sb + OFF_LSUM + p * 4, 0.f);
              }
            } else {
              const uint32_t o = sb + OFF_LPART + lane * 8;
              if (lane < 24) {
                float2 v[3][4];
#pragma unroll
                for (int h = 0; h < 3; h++)
#pragma unroll
                  for (int q = 0; q < 4; q++) v[h][q] = lds64(o + h * 192 + q * 576);
                float2 a[3];
#pragma unroll
                for (int h = 0; h < 3; h++) a[h] = make_float2((v[h][0].x + v[h][1].x) + (v[h][2].x + v[h][3].x), (v[h][0].y + v[h][1].y) + (v[h][2].y + v[h][3].y));
#pragma unroll
                for (int h = 0; h < 3; h++)
#pragma unroll
                  for (int q = 0; q < 4; q++) v[h][q] = lds64(o + h * 192 + (q + 4) * 576);
#pragma unroll
                for (int h = 0; h < 3; h++) {
                  const float l0 = a[h].x + ((v[h][0].x + v[h][1].x) + (v[h][2].x + v[h][3].x));
                  const float l1 = a[h].y + ((v[h][0].y + v[h][1].y) + (v[h][2].y + v[h][3].y));
                  bad |= !(l0 >= 1.f && l0 <= L_MAX && l1 >= 1.f && l1 <= L_MAX);
                  asm volatile("st.shared.v2.f32 [%0], {%1, %2};" ::"r"(o + h * 192), "f"(rcp(l0)), "f"(rcp(l1)) : "memory");
                }
              }
            }
            bad = __any_sync(0xffffffffu, bad);
          }
          if (lane == 0) {
            uint32_t sel;
            if (r < 8) mbar_arrive(sb + BAR_LREADY);
            TRACE_P(40);
#pragma unroll 1
            for (int h = 0; h < 2; h++) {
              mbar_wait(sb + BAR_OSTG + h * 8, (pass + r) & 1);
              TRACE_P(41);
              sel = lds32u(sb + OFF_SEL);
              const int w = 2 * (R % OSLOTS) + h;
              if (r == 8) tma_store(&maps.out, br * 512 + c * 128 + 64 * h, b * SQ, sb + OFF_Q + h * B_BYTES);
              else if (!DBG_NOOX) tma_store3(&maps.o, ((sel >> w) & 1) * 64, (cta * NWIN + w) * 4, sb + OFF_Q + h * B_BYTES);
              if (h == 0 && r >= 7) continue;
              asm volatile("cp.async.bulk.commit_group;" ::: "memory");
              asm volatile("cp.async.bulk.wait_group 0;" ::: "memory");
              mbar_arrive(sb + BAR_QFREE + h * 8);
              if (r >= 7) mbar_arrive(sb + BAR_QFREE);
              TRACE_P(43);
            }
            bad |= lds32u(sb + OFF_INFO + 4);
            if (r < 8) {
              const unsigned long long f = ((unsigned long long)sel << 32) | (base + 2 * (R + 1) + (pass ? 0 : bad));
              if (CFG_RELEASE) asm volatile("st.release.gpu.global.u64 [%0], %1;" ::"l"(&g_flag[cta * 16]), "l"(f) : "memory");
              else asm volatile("st.relaxed.gpu.global.u64 [%0], %1;" ::"l"(&g_flag[cta * 16]), "l"(f) : "memory");
            }
            TRACE_P(44);
          }
          __syncwarp();
        }
        if (pass) break;
        mbar_wait(sb + BAR_REDO, 0);
        if (!lds32u(sb + OFF_INFO + 8)) break;
      }
    }
  } else {
    asm volatile("setmaxnreg.inc.sync.aligned.u32 %0;" ::"n"(CFG_CREG));
    const uint32_t x = warp >> 2;
    Consumer cs;
    cs.sb = sb;
    cs.abar = sb + BAR_FULLA + x * NA * 8;
    cs.adesc = desc_lo(sb + OFF_A + x * NA * A_BYTES);
    cs.lane0 = lane == 0;
    const uint32_t st_off = ((lane >> 4) * 8 + (lane & 7)) * 128 + (((2 * (warp & 3) + ((lane >> 3) & 1)) ^ (lane & 7)) << 4);
    const uint32_t v_off = (lane & 3) * 16;
    const uint32_t r_off = (16 * (lane >> 4) + 4 * (lane & 3) + ((lane >> 2) & 3)) * 4;
    float4* const accp = g_acc + (size_t)cta * 18 * 256 + tid;

    auto run = [&](auto pass_c) {
    constexpr uint32_t pass = decltype(pass_c)::value;
    float accA[72], accB[72], l[36];
#pragma unroll
    for (int i = 0; i < 72; i++) { accA[i] = 0.f; accB[i] = 0.f; }
#pragma unroll
    for (int i = 0; i < 36; i++) l[i] = 0.f;
    uint32_t o16[36];
    float osc = 1.f;
#pragma unroll
    for (int i = 0; i < 36; i++) o16[i] = 0;
    Cursor<NB> pw;
    uint32_t kready = 0;

    auto pv = [&](int t) {
      if (__builtin_expect(pass && t > 0, 0)) {
        mbar_wait(sb + BAR_FULLB + cs.bc.slot * 8, cs.bc.ph);
        wg_wait<0>();
        pin(accB);
#pragma unroll
        for (int jj = 0; jj < 9; jj++) {
          const int i = 8 * jj;
          const float4 f = lds128(sb + OFF_FAC + (t % NFAC) * 576 + v_off + jj * 64);
          accB[i] *= f.x; accB[i + 1] *= f.y; accB[i + 2] *= f.x; accB[i + 3] *= f.y;
          accB[i + 4] *= f.z; accB[i + 5] *= f.w; accB[i + 6] *= f.z; accB[i + 7] *= f.w;
        }
      }
      cs.step(accB, t != 0);
    };

#pragma unroll 1
    for (int it = 0;; it++) {
      const int j = it & 3, r = it >> 2;
      const int n = n_op(r);
      if (j == 0) {
        TRACE_R(r);
        if (r > 0) {
#pragma unroll 1
          for (int t = 4 + 2 * x; t < 8; t++) {
            pv(t);
            if (t == (pass ? 7 : (x ? CFG_TLB : CFG_TLA))) {
              float l5[5];
              col_reduce<false>(l, l5, lane);
              if (__builtin_expect(pass, 0)) {
#pragma unroll
                for (int G = 0; G < 5; G++) {
                  const uint32_t o = G < 4 ? r_off + G * 128 : (r_off & 63) + 512;
                  if (x == 0) l5[G] *= lds32(sb + OFF_FAC + (7 % NFAC) * 576 + o);
                  if (G < 4 || lane < 16) asm volatile("red.shared.add.f32 [%0], %1;" ::"r"(sb + OFF_LSUM + o), "f"(l5[G]) : "memory");
                }
              } else {
                const uint32_t ls = sb + OFF_LPART + warp * 576 + r_off;
#pragma unroll
                for (int G = 0; G < 4; G++) sts32(ls + G * 128, l5[G]);
                if (lane < 16) sts32(ls + 512, l5[4]);
              }
              __syncwarp();
              mbar_arrive_if(sb + BAR_LFULL, cs.lane0);
              TRACE(8);
            }
            wg_wait<1>();
            cs.rel_ab(t > 4 + 2 * (int)x);
          }
          TRACE(1);
        }
        const int ko = r == 0 ? -1 : (r == 8 ? 0 : (x ? CFG_KB : CFG_KA));
        if (__builtin_expect(r == 8, 0)) {
          if (pass) {
#pragma unroll
            for (int i = 0; i < 18; i++) {
              const float4 v = __ldcg(accp + i * 256);
              accA[4 * i] = v.x; accA[4 * i + 1] = v.y; accA[4 * i + 2] = v.z; accA[4 * i + 3] = v.w;
            }
          } else {
            const float inv = rcp(osc);
#pragma unroll
            for (int i = 0; i < 36; i++) {
              const float2 v = __half22float2(*reinterpret_cast<const __half2*>(&o16[i]));
              accA[2 * i] = v.x * inv; accA[2 * i + 1] = v.y * inv;
            }
          }
        } else {
          cs.step(accA, 0);
          wg_wait<1>();
          cs.rel_ab(r > 0);
        }
#pragma unroll 1
        for (int i = r < 8; i < (r < 8 ? 8 : 8 + OPD); i++) {
          cs.step(accA, 1);
          wg_wait<1>();
          cs.rel_ab();
          if (i == ko) {
            TRACE(2);
            pin(accB);
            mbar_wait(sb + BAR_LREADY, (r - 1) & 1);
            float4 fq[9];
#pragma unroll
            for (int jj = 0; jj < 9; jj++) fq[jj] = lds128(sb + OFF_LINV + v_off + jj * 64);
            uint32_t chk = 0;
#pragma unroll
            for (int jj = 0; jj < 9; jj++) {
              const int q = 8 * jj;
              const float4 f = fq[jj];
              const uint32_t r0 = pack_bf16(accB[q] * f.x, accB[q + 1] * f.y), r1 = pack_bf16(accB[q + 2] * f.x, accB[q + 3] * f.y);
              const uint32_t r2 = pack_bf16(accB[q + 4] * f.z, accB[q + 5] * f.w), r3 = pack_bf16(accB[q + 6] * f.z, accB[q + 7] * f.w);
              stsm_t(sb + OFF_Q + x * B_BYTES + st_off + jj * 2048, r0, r1, r2, r3);
              asm("fma.rn.bf16x2 %0, %1, %2, %0;" : "+r"(chk) : "r"(r0), "r"(r1));
              asm("fma.rn.bf16x2 %0, %1, %2, %0;" : "+r"(chk) : "r"(r2), "r"(r3));
            }
            if ((chk & 0x7F80u) == 0x7F80u || (chk & 0x7F800000u) == 0x7F800000u) sts32u(sb + OFF_INFO + 4, 1);
            fence_async_smem();
            __syncwarp();
            mbar_arrive_if(sb + BAR_OSTG + x * 8, cs.lane0);
            TRACE(3);
          }
        }
        TRACE(4);
        pw = cs.bc;
        pw.skip(n + x);
        const int n1 = n ? n - 4 + 2 * (int)x : 1, kq = n && x ? CFG_QB : 0;
#pragma unroll 1
        for (int i = 0; i < n1; i++) {
          if (n) { cs.step(accB, i > 0); wg_wait<1>(); } else { wg_wait<0>(); }
          cs.rel_ab();
          if (i == kq) {
            TRACE(5);
            pin(accA);
            if (r + pass > 0) mbar_wait(sb + BAR_QFREE + x * 8, (pass + r - 1) & 1);
            const float qs = (pass || r == 8) ? 1.f : SCL;
#pragma unroll
            for (int jj = 0; jj < 9; jj++) {
              const int q = 8 * jj;
              stsm_t(sb + OFF_Q + x * B_BYTES + st_off + jj * 2048, pack_bf16(accA[q] * qs, accA[q + 1] * qs),
                     pack_bf16(accA[q + 2] * qs, accA[q + 3] * qs), pack_bf16(accA[q + 4] * qs, accA[q + 5] * qs),
                     pack_bf16(accA[q + 6] * qs, accA[q + 7] * qs));
            }
            fence_async_smem();
            __syncwarp();
            mbar_arrive_if(sb + (r == 8 ? BAR_OSTG + x * 8 : BAR_QFULL), cs.lane0);
            TRACE(6);
          }
        }
#pragma unroll
        for (int i = 0; i < 36; i++) l[i] = 0.f;
        TRACE(r == 8 ? 21 : 7);
        if (r == 8) {
          wg_wait<0>();
          break;
        }
        mbar_wait(sb + BAR_QFULL, r & 1);
        kready = 0;
        if (CFG_ORDER && x) asm volatile("bar.sync 3, 256;" ::: "memory");
      }
      const int t = 2 * j + x;
      cs.step_s(accA, kready);
      if (CFG_ORDER == 1 && t == 0) asm volatile("bar.arrive 3, 256;" ::: "memory");
      TRACE(10);
      const int tp = 2 * (j + (int)x) - 4;
      if (tp == 0 && n && !(DBG_NOFLUSH && r > 1)) {
        wg_wait<1>();
        pin(accB);
        if (__builtin_expect(pass, 0)) {
          if (r == R1) {
#pragma unroll
            for (int i = 0; i < 18; i++) accp[i * 256] = make_float4(accB[4 * i], accB[4 * i + 1], accB[4 * i + 2], accB[4 * i + 3]);
          } else {
#pragma unroll
            for (int i = 0; i < 18; i++)
              asm volatile("red.global.add.v4.f32 [%0], {%1, %2, %3, %4};" ::"l"(accp + i * 256), "f"(accB[4 * i]),
                           "f"(accB[4 * i + 1]), "f"(accB[4 * i + 2]), "f"(accB[4 * i + 3]) : "memory");
          }
        } else {
          if (__builtin_expect(r == R1, 0)) {
            float m = 0.f;
#pragma unroll
            for (int i = 0; i < 72; i++) m = fmaxf(m, fabsf(accB[i]));
            const uint32_t e = min(max(__float_as_uint(m) >> 23, 20u), 240u);
            osc = __uint_as_float((258u - e) << 23);
          }
#pragma unroll
          for (int i = 0; i < 36; i++) {
            uint32_t h;
            asm("cvt.rn.f16x2.f32 %0, %1, %2;" : "=r"(h) : "f"(accB[2 * i + 1] * osc), "f"(accB[2 * i] * osc));
            asm("add.rn.f16x2 %0, %0, %1;" : "+r"(o16[i]) : "r"(h));
          }
          if (__builtin_expect(r == 7, 0)) {
            uint32_t chk = 0;
#pragma unroll
            for (int i = 0; i < 36; i++) asm("fma.rn.f16x2 %0, %1, %2, %0;" : "+r"(chk) : "r"(o16[i]), "r"(0u));
            if (chk & 0x7C007C00u) sts32u(sb + OFF_INFO + 4, 1);
          }
        }
        TRACE(11);
      }
      const uint32_t trail = tp >= 0 || n;
      uint32_t pfree;
      if (trail) {
        pv(tp);
        pfree = mbar_test(sb + BAR_EMPTYB + pw.slot * 8, pw.ph ^ 1);
        pv(tp + 1);
        if (CFG_ORDER == 2 && t == 0) asm volatile("bar.arrive 3, 256;" ::: "memory");
        wg_wait<2>();
      } else {
        if (CFG_ORDER == 2 && t == 0) asm volatile("bar.arrive 3, 256;" ::: "memory");
        pfree = 0;
        wg_wait<0>();
      }
      pin(accA);
      TRACE(12);
      cs.rel_ab(j == 0 && n);
      if (!pfree) mbar_wait(sb + BAR_EMPTYB + pw.slot * 8, pw.ph ^ 1);
      const uint32_t ptile = sb + OFF_B + pw.slot * B_BYTES + st_off;
      TRACE(13);

      if (__builtin_expect(pass, 0)) {
        const uint32_t mo = sb + OFF_M + ((t + 1) & 1) * 576, mn = sb + OFF_M + (t & 1) * 576;
        const uint32_t wt = tid & 127;
        float lm[36], m5[5];
#pragma unroll
        for (int i = 0; i < 18; i++) {
          lm[2 * i] = fmaxf(accA[4 * i], accA[4 * i + 2]);
          lm[2 * i + 1] = fmaxf(accA[4 * i + 1], accA[4 * i + 3]);
        }
        col_reduce<true>(lm, m5, lane);
        if (t > 0) {
          const uint32_t ps = pw.slot == 0 ? NB - 1 : pw.slot - 1;
          mbar_wait(sb + BAR_FULLB + ps * 8, pw.slot == 0 ? pw.ph ^ 1 : pw.ph);
        }
        sts32(mn + wt * 4, M_INIT);
        if (wt < 16) sts32(mn + 512 + wt * 4, M_INIT);
        bar_sync(1 + x);
#pragma unroll
        for (int G = 0; G < 5; G++) {
          const uint32_t o = G < 4 ? r_off + G * 128 : (r_off & 63) + 512;
          float v = m5[G] * SCL;
          if (t > 0) v = fmaxf(v, lds32(mo + o));
          if (v >= 0.f) asm volatile("red.shared.max.s32 [%0], %1;" ::"r"(mn + o), "r"(__float_as_int(v)) : "memory");
          else asm volatile("red.shared.min.u32 [%0], %1;" ::"r"(mn + o), "r"(__float_as_uint(v)) : "memory");
        }
        bar_sync(1 + x);
        if (t > 0) {
          const uint32_t f = sb + OFF_FAC + (t % NFAC) * 576;
          sts32(f + wt * 4, ex2(lds32(mo + wt * 4) - lds32(mn + wt * 4)));
          if (wt < 16) sts32(f + 512 + wt * 4, ex2(lds32(mo + 512 + wt * 4) - lds32(mn + 512 + wt * 4)));
          bar_sync(1 + x);
        }
#pragma unroll
        for (int jj = 0; jj < 9; jj++) {
          const int i = 8 * jj;
          if (t > 1) {
            const float4 f0 = lds128(sb + OFF_FAC + ((t - 1) % NFAC) * 576 + v_off + jj * 64);
            const float4 f1 = lds128(sb + OFF_FAC + (t % NFAC) * 576 + v_off + jj * 64);
            l[4 * jj] *= f0.x * f1.x; l[4 * jj + 1] *= f0.y * f1.y; l[4 * jj + 2] *= f0.z * f1.z; l[4 * jj + 3] *= f0.w * f1.w;
          }
          const float4 m = lds128(mn + v_off + jj * 64);
          const float p0 = ex2(fmaf(accA[i], SCL, -m.x)), p1 = ex2(fmaf(accA[i + 1], SCL, -m.y));
          const float p2 = ex2(fmaf(accA[i + 2], SCL, -m.x)), p3 = ex2(fmaf(accA[i + 3], SCL, -m.y));
          const float p4 = ex2(fmaf(accA[i + 4], SCL, -m.z)), p5 = ex2(fmaf(accA[i + 5], SCL, -m.w));
          const float p6 = ex2(fmaf(accA[i + 6], SCL, -m.z)), p7 = ex2(fmaf(accA[i + 7], SCL, -m.w));
          stsm_t(ptile + jj * 2048, pack_bf16(p0, p1), pack_bf16(p2, p3), pack_bf16(p4, p5), pack_bf16(p6, p7));
          l[4 * jj] += p0 + p2; l[4 * jj + 1] += p1 + p3; l[4 * jj + 2] += p4 + p6; l[4 * jj + 3] += p5 + p7;
        }
        cs.rel_a();
        cs.rel_a();
        wg_wait<0>();
        cs.rel_ab(trail);
        cs.rel_ab(trail);
        kready = 0;
      } else {
        cs.rel_a();
        cs.rel_a();
#pragma unroll
        for (int jj = 0; jj < 9; jj++) {
          const int i = 8 * jj;
          const float p0 = ex2(accA[i]), p1 = ex2(accA[i + 1]), p2 = ex2(accA[i + 2]), p3 = ex2(accA[i + 3]);
          const float p4 = ex2(accA[i + 4]), p5 = ex2(accA[i + 5]), p6 = ex2(accA[i + 6]), p7 = ex2(accA[i + 7]);
          stsm_t(ptile + jj * 2048, pack_bf16(p0, p1), pack_bf16(p2, p3), pack_bf16(p4, p5), pack_bf16(p6, p7));
          l[4 * jj] += p0 + p2; l[4 * jj + 1] += p1 + p3; l[4 * jj + 2] += p4 + p6; l[4 * jj + 3] += p5 + p7;
          if (jj == 6) {
            wg_wait<0>();
            cs.rel_ab(trail);
            cs.rel_ab(trail);
            kready = cs.test_s();
          }
        }
      }
      __syncwarp();
      mbar_arrive_if(sb + BAR_PSTG + (t & 3) * 8, cs.lane0);
      pw.skip(2);
      TRACE(14);
    }
    };
    run(Const<0>());
    mbar_wait(sb + BAR_REDO, 0);
    if (!DBG_NOSAFE && __shfl_sync(0xffffffffu, lds32u(sb + OFF_INFO + 8), 0)) run(Const<1>());
  }
}

typedef CUresult (*EncodeFn)(CUtensorMap*, CUtensorMapDataType, cuuint32_t, void*, const cuuint64_t*, const cuuint64_t*,
                             const cuuint32_t*, const cuuint32_t*, CUtensorMapInterleave, CUtensorMapSwizzle,
                             CUtensorMapL2promotion, CUtensorMapFloatOOBfill);

void make_map(EncodeFn enc, CUtensorMap* m, const void* base, uint64_t cols, uint64_t rows, uint32_t box_rows) {
  cuuint64_t dims[2] = {cols, rows};
  cuuint64_t strides[1] = {cols * 2};
  cuuint32_t box[2] = {64, box_rows};
  cuuint32_t es[2] = {1, 1};
  enc(m, CU_TENSOR_MAP_DATA_TYPE_BFLOAT16, 2, const_cast<void*>(base), dims, strides, box, es, CU_TENSOR_MAP_INTERLEAVE_NONE,
      CU_TENSOR_MAP_SWIZZLE_128B, CFG_PROMO, CU_TENSOR_MAP_FLOAT_OOB_FILL_NONE);
}

}

extern "C" void kernel_launch(void* const* d_in, const int* in_sizes, int n_in, void* d_out, int out_size) {
  (void)in_sizes; (void)n_in; (void)out_size;
  void* fn = nullptr;
  cudaDriverEntryPointQueryResult st;
  cudaGetDriverEntryPoint("cuTensorMapEncodeTiled", &fn, cudaEnableDefault, &st);
  EncodeFn enc = (EncodeFn)fn;
  void* scr = nullptr;
  cudaGetSymbolAddress(&scr, g_scr);
  Maps maps;
  Ptrs ptrs;
  ptrs.scr = (char*)(((uintptr_t)scr + 65535) & ~(uintptr_t)65535);
  for (int br = 0; br < 2; br++) {
    make_map(enc, &maps.x[br], d_in[5 * br + 0], 512, 16 * SQ, SQ);
    make_map(enc, &maps.k[br], d_in[5 * br + 1], 128, 16 * 32 * 512, 64);
    make_map(enc, &maps.v[br], d_in[5 * br + 2], 128, 16 * 32 * 512, 64);
    make_map(enc, &maps.wq[br], d_in[5 * br + 3], 4096, 512, 64);
    make_map(enc, &maps.wo[br], d_in[5 * br + 4], 512, 4096, 64);
    ptrs.k[br] = (const char*)d_in[5 * br + 1];
    ptrs.v[br] = (const char*)d_in[5 * br + 2];
    ptrs.wq[br] = (const char*)d_in[5 * br + 3];
    ptrs.wo[br] = (const char*)d_in[5 * br + 4];
  }
  {
    cuuint64_t dims[3] = {64, 128, (cuuint64_t)128 * NWIN * 4 - 1};
    cuuint64_t strides[2] = {128, 16384};
    cuuint32_t box[3] = {64, 48, 3};
    cuuint32_t es[3] = {1, 1, 1};
    enc(&maps.o, CU_TENSOR_MAP_DATA_TYPE_BFLOAT16, 3, ptrs.scr + 4096, dims, strides, box, es, CU_TENSOR_MAP_INTERLEAVE_NONE,
        CU_TENSOR_MAP_SWIZZLE_128B, CFG_PROMO, CU_TENSOR_MAP_FLOAT_OOB_FILL_NONE);
  }
  make_map(enc, &maps.out, d_out, 1024, 16 * SQ, SQ);
  cudaFuncSetAttribute(fused_mha_kernel, cudaFuncAttributeMaxDynamicSharedMemorySize, SMEM_BYTES);
  cudaLaunchConfig_t cfg = {};
  cfg.gridDim = dim3(128);
  cfg.blockDim = dim3(384);
  cfg.dynamicSmemBytes = SMEM_BYTES;
  cfg.stream = cudaStreamPerThread;
  cudaLaunchAttribute at[1];
  at[0].id = cudaLaunchAttributeClusterDimension;
  at[0].val.clusterDim.x = CFG_MC ? 2 : 1;
  at[0].val.clusterDim.y = 1;
  at[0].val.clusterDim.z = 1;
  cfg.attrs = at;
  cfg.numAttrs = CFG_MC ? 1 : 0;
  cudaLaunchKernelEx(&cfg, fused_mha_kernel, maps, ptrs);
}
```

```cpp
#include <cuda_runtime.h>
#include <cuda.h>
#include <cuda_bf16.h>
#include <cuda_fp16.h>
#include <stdint.h>

namespace {

constexpr int SQ = 144;
constexpr int NA = 6;
constexpr int NB = 5;
constexpr int NWIN = 4;
constexpr int R1 = 2;
constexpr int KA = 2, KB = 4, FA = 2, FB = 0;
constexpr uint32_t STAGGER = 9500, PF_STEP = 520, PF_LATE = 10500;

constexpr uint32_t A_BYTES = 8192, B_BYTES = 18432;
constexpr uint32_t OFF_A = 0;
constexpr uint32_t OFF_B = 2 * NA * A_BYTES;
constexpr uint32_t OFF_Q = OFF_B + NB * B_BYTES;
constexpr uint32_t OFF_LPART = OFF_Q + 2 * B_BYTES;
constexpr uint32_t OFF_LINV = OFF_LPART;
constexpr uint32_t OFF_LSUM = OFF_LPART + 576;
constexpr uint32_t OFF_M = OFF_LSUM + 576;
constexpr uint32_t OFF_FAC = OFF_M + 2 * 576;
constexpr uint32_t OFF_SEL = OFF_LPART + 8 * 576;
constexpr uint32_t OFF_BAD = OFF_SEL + 4;
constexpr uint32_t OFF_REDO = OFF_SEL + 8;
constexpr uint32_t BAR_FULLA = OFF_SEL + 16;
constexpr uint32_t BAR_EMPTYA = BAR_FULLA + 2 * NA * 8;
constexpr uint32_t BAR_FULLB = BAR_EMPTYA + 2 * NA * 8;
constexpr uint32_t BAR_EMPTYB = BAR_FULLB + NB * 8;
constexpr uint32_t BAR_PGATE = BAR_EMPTYB + NB * 8;
constexpr uint32_t BAR_PEER = BAR_PGATE + NB * 8;
constexpr uint32_t BAR_PEERA = BAR_PEER + NB * 8;
constexpr uint32_t BAR_QFREE = BAR_PEERA + 2 * NA * 8;
constexpr uint32_t BAR_QFULL = BAR_QFREE + 16;
constexpr uint32_t BAR_LREADY = BAR_QFULL + 8;
constexpr uint32_t BAR_SEL = BAR_LREADY + 8;
constexpr uint32_t BAR_REDO = BAR_SEL + 8;
constexpr uint32_t BAR_END = BAR_REDO + 8;
constexpr uint32_t NB_PSTG = 4, NB_OSTG = 8, NB_LFULL = 10;
constexpr uint32_t SMEM_BYTES = 232448;
static_assert(BAR_END <= SMEM_BYTES, "shared memory budget");
constexpr uint32_t EA = BAR_EMPTYA - BAR_FULLA, EB = BAR_EMPTYB - BAR_FULLB;

constexpr float SCL = 0.08838834764831845f * 1.4426950408889634f;
constexpr float L_MAX = 1099511627776.f;
constexpr float M_INIT = -3.0e38f;

struct Maps {
  CUtensorMap x[2], wq[2], k[2], v[2], wo[2], o, o1, out;
};
struct Ptrs {
  const char *x[2], *k[2], *v[2], *wq[2];
  char* scr;
};

__device__ uint4 g_scr[(128 * NWIN + 1) * 4096];
__device__ float4 g_acc[128 * 18 * 256];
__device__ unsigned long long g_flag[128 * 16];

__device__ __forceinline__ void mbar_init(uint32_t bar, uint32_t cnt) {
  asm volatile("mbarrier.init.shared::cta.b64 [%0], %1;" ::"r"(bar), "r"(cnt));
}
__device__ __forceinline__ void mbar_arrive_if(uint32_t bar, uint32_t pred) {
  asm volatile("{\n.reg .pred p;\nsetp.ne.u32 p, %1, 0;\n@p mbarrier.arrive.shared::cta.b64 _, [%0];\n}" ::"r"(bar), "r"(pred) : "memory");
}
#define SPIN_TAIL "@p bra WD;\nadd.u32 c, c, 1;\nsetp.lt.u32 p, c, 4194304;\n@p bra WL;\ntrap;\nWD:\n}"
__device__ __forceinline__ void mbar_wait(uint32_t bar, uint32_t parity) {
  asm volatile("{\n.reg .pred p;\n.reg .u32 c;\nmov.u32 c, 0;\nWL:\n"
               "mbarrier.try_wait.parity.shared::cta.b64 p, [%0], %1;\n" SPIN_TAIL ::"r"(bar), "r"(parity) : "memory");
}
__device__ __forceinline__ void mbar_wait2(uint32_t b0, uint32_t p0, uint32_t b1, uint32_t p1) {
  asm volatile("{\n.reg .pred p, q;\n.reg .u32 c;\nmov.u32 c, 0;\nWL:\n"
               "mbarrier.try_wait.parity.shared::cta.b64 p, [%0], %1;\n"
               "mbarrier.try_wait.parity.shared::cta.b64 q, [%2], %3;\n"
               "and.pred p, p, q;\n" SPIN_TAIL ::"r"(b0), "r"(p0), "r"(b1), "r"(p1) : "memory");
}
__device__ __forceinline__ void mbar_wait3(uint32_t b0, uint32_t p0, uint32_t b1, uint32_t p1, uint32_t b2, uint32_t p2) {
  asm volatile("{\n.reg .pred p, q, r;\n.reg .u32 c;\nmov.u32 c, 0;\nWL:\n"
               "mbarrier.try_wait.parity.shared::cta.b64 p, [%0], %1;\n"
               "mbarrier.try_wait.parity.shared::cta.b64 q, [%2], %3;\n"
               "mbarrier.try_wait.parity.shared::cta.b64 r, [%4], %5;\n"
               "and.pred p, p, q;\nand.pred p, p, r;\n" SPIN_TAIL ::"r"(b0), "r"(p0), "r"(b1), "r"(p1), "r"(b2), "r"(p2) : "memory");
}
__device__ __forceinline__ uint32_t mbar_test(uint32_t bar, uint32_t parity) {
  uint32_t ok;
  asm volatile("{\n.reg .pred p;\nmbarrier.test_wait.parity.shared::cta.b64 p, [%1], %2;\nselp.u32 %0, 1, 0, p;\n}"
               : "=r"(ok) : "r"(bar), "r"(parity) : "memory");
  return ok;
}
#define ELECT "{\n.reg .pred p;\nelect.sync _|p, 0xffffffff;\n"
__device__ __forceinline__ void tma_load_hint(uint32_t dst, const CUtensorMap* map, int c0, int c1, uint32_t bar, uint64_t pol) {
  asm volatile(ELECT
               "@p cp.async.bulk.tensor.2d.shared::cluster.global.mbarrier::complete_tx::bytes.L2::cache_hint [%0], [%1, {%3, %4}], [%2], %6;\n"
               "@p mbarrier.arrive.expect_tx.shared::cta.b64 _, [%2], %5;\n}"
               ::"r"(dst), "l"(map), "r"(bar), "r"(c0), "r"(c1), "n"(A_BYTES), "l"(pol) : "memory");
}
template <uint32_t BYTES>
__device__ __forceinline__ void tma_multicast2(uint32_t dst, const CUtensorMap* map, int c0, int c1, uint32_t bar, uint32_t mask) {
  asm volatile(ELECT
               "@p cp.async.bulk.tensor.2d.shared::cluster.global.mbarrier::complete_tx::bytes.multicast::cluster [%0], [%1, {%3, %4}], [%2], %5;\n"
               "@p mbarrier.arrive.expect_tx.shared::cta.b64 _, [%2], %6;\n}"
               ::"r"(dst), "l"(map), "r"(bar), "r"(c0), "r"(c1), "h"((uint16_t)mask), "n"(BYTES) : "memory");
}
__device__ __forceinline__ void tma_multicast3(uint32_t dst, const CUtensorMap* map, int c1, int c2, uint32_t bar, uint32_t mask) {
  asm volatile(ELECT
               "@p cp.async.bulk.tensor.3d.shared::cluster.global.mbarrier::complete_tx::bytes.multicast::cluster [%0], [%1, {0, %3, %4}], [%2], %5;\n"
               "@p mbarrier.arrive.expect_tx.shared::cta.b64 _, [%2], %6;\n}"
               ::"r"(dst), "l"(map), "r"(bar), "r"(c1), "r"(c2), "h"((uint16_t)mask), "n"(B_BYTES) : "memory");
}
template <uint32_t BYTES>
__device__ __forceinline__ void relay_slot(uint32_t bar, uint32_t peer_bar, uint32_t rank) {
  asm volatile(ELECT ".reg .b32 ra;\nmapa.shared::cluster.u32 ra, %1, %2;\n"
               "@p mbarrier.arrive.shared::cluster.b64 _, [ra];\n"
               "@p mbarrier.arrive.expect_tx.shared::cta.b64 _, [%0], %3;\n}" ::"r"(bar), "r"(peer_bar), "r"(rank), "n"(BYTES) : "memory");
}
__device__ __forceinline__ void tma_store2(const CUtensorMap* map, int c0, int c1, uint32_t src) {
  asm volatile(ELECT "@p cp.async.bulk.tensor.2d.global.shared::cta.bulk_group [%0, {%2, %3}], [%1];\n}"
               ::"l"(map), "r"(src), "r"(c0), "r"(c1) : "memory");
}
__device__ __forceinline__ void tma_store3(const CUtensorMap* map, int c1, int c2, uint32_t src) {
  asm volatile(ELECT "@p cp.async.bulk.tensor.3d.global.shared::cta.bulk_group [%0, {0, %2, %3}], [%1];\n}"
               ::"l"(map), "r"(src), "r"(c1), "r"(c2) : "memory");
}
__device__ __forceinline__ void bulk_prefetch(const void* p, uint32_t bytes) {
  asm volatile("cp.async.bulk.prefetch.L2.global [%0], %1;" ::"l"(p), "r"(bytes) : "memory");
}
__device__ __forceinline__ void prefetch_l2(const void* p) { asm volatile("prefetch.global.L2 [%0];" ::"l"(p)); }
__device__ __forceinline__ void fence_async_smem() { asm volatile("fence.proxy.async.shared::cta;" ::: "memory"); }
__device__ __forceinline__ void fence_async_global() { asm volatile("fence.proxy.async.global;" ::: "memory"); }
__device__ __forceinline__ uint32_t clock32() { uint32_t t; asm volatile("mov.u32 %0, %%clock;" : "=r"(t)::"memory"); return t; }
__device__ __forceinline__ void wait_until(uint32_t t) { while ((int)(clock32() - t) < 0) __nanosleep(50); }
__device__ __forceinline__ void wg_fence() { asm volatile("wgmma.fence.sync.aligned;" ::: "memory"); }
__device__ __forceinline__ void wg_commit() { asm volatile("wgmma.commit_group.sync.aligned;" ::: "memory"); }
template <int N> __device__ __forceinline__ void wg_wait() { asm volatile("wgmma.wait_group.sync.aligned %0;" ::"n"(N) : "memory"); }
__device__ __forceinline__ void pin(float (&d)[72]) {
#pragma unroll
  for (int i = 0; i < 72; i++) asm volatile("" : "+f"(d[i])::"memory");
}
template <int N> __device__ __forceinline__ void bar_sync(uint32_t id) { asm volatile("bar.sync %0, %1;" ::"r"(id), "n"(N) : "memory"); }
template <int N> __device__ __forceinline__ void bar_arrive(uint32_t id) { asm volatile("bar.arrive %0, %1;" ::"r"(id), "n"(N) : "memory"); }
__device__ __forceinline__ float ex2(float x) { float y; asm("ex2.approx.ftz.f32 %0, %1;" : "=f"(y) : "f"(x)); return y; }
__device__ __forceinline__ float rcp(float x) { float y; asm("rcp.approx.f32 %0, %1;" : "=f"(y) : "f"(x)); return y; }
__device__ __forceinline__ uint32_t pack_bf16(float lo, float hi) {
  uint32_t r; asm("cvt.rn.bf16x2.f32 %0, %1, %2;" : "=r"(r) : "f"(hi), "f"(lo)); return r;
}
__device__ __forceinline__ uint32_t add_bf16x2(uint32_t a, uint32_t b) {
  uint32_t r; asm("add.rn.bf16x2 %0, %1, %2;" : "=r"(r) : "r"(a), "r"(b)); return r;
}
__device__ __forceinline__ void stsm_t(uint32_t addr, uint32_t r0, uint32_t r1, uint32_t r2, uint32_t r3) {
  asm volatile("stmatrix.sync.aligned.m8n8.x4.trans.shared.b16 [%0], {%1, %2, %3, %4};"
               ::"r"(addr), "r"(r0), "r"(r1), "r"(r2), "r"(r3) : "memory");
}
__device__ __forceinline__ float4 lds128(uint32_t a) {
  float4 v; asm volatile("ld.shared.v4.f32 {%0, %1, %2, %3}, [%4];" : "=f"(v.x), "=f"(v.y), "=f"(v.z), "=f"(v.w) : "r"(a) : "memory"); return v;
}
__device__ __forceinline__ float2 lds64(uint32_t a) {
  float2 v; asm volatile("ld.shared.v2.f32 {%0, %1}, [%2];" : "=f"(v.x), "=f"(v.y) : "r"(a) : "memory"); return v;
}
__device__ __forceinline__ float lds32(uint32_t a) { float v; asm volatile("ld.shared.f32 %0, [%1];" : "=f"(v) : "r"(a) : "memory"); return v; }
__device__ __forceinline__ uint32_t lds32u(uint32_t a) { uint32_t v; asm volatile("ld.shared.u32 %0, [%1];" : "=r"(v) : "r"(a) : "memory"); return v; }
__device__ __forceinline__ uint32_t lds_uniform(uint32_t a) { return __shfl_sync(0xffffffffu, lds32u(a), 0); }
__device__ __forceinline__ void sts32(uint32_t a, float v) { asm volatile("st.shared.f32 [%0], %1;" ::"r"(a), "f"(v) : "memory"); }
__device__ __forceinline__ void sts32u(uint32_t a, uint32_t v) { asm volatile("st.shared.u32 [%0], %1;" ::"r"(a), "r"(v) : "memory"); }

__device__ __forceinline__ uint32_t nearer_placement(char* win) {
  uint32_t votes = 0;
#pragma unroll 1
  for (int i = 0; i < 3; i++) {
    uint32_t t0, t1, v0, v1;
    asm volatile("atom.relaxed.gpu.global.exch.b32 %0, [%2], %3;\n\tatom.relaxed.gpu.global.exch.b32 %1, [%2+8192], %3;"
                 : "=r"(v0), "=r"(v1) : "l"(win + 53248), "r"(i) : "memory");
    asm volatile("{\n.reg .pred p;\nsetp.eq.u32 p, %1, 0xffffffff;\n@p mov.u32 %0, 0;\n@!p mov.u32 %0, %%clock;\n}" : "=r"(t0) : "r"(v0) : "memory");
    asm volatile("{\n.reg .pred p;\nsetp.eq.u32 p, %1, 0xffffffff;\n@p mov.u32 %0, 0;\n@!p mov.u32 %0, %%clock;\n}" : "=r"(t1) : "r"(v1) : "memory");
    votes += t1 - t0 < 90;
  }
  return votes >= 2;
}

#define WGMMA                                                                                   \
  "wgmma.mma_async.sync.aligned.m64n144k16.f32.bf16.bf16 "                                      \
  "{%0, %1, %2, %3, %4, %5, %6, %7, %8, %9, %10, %11, %12, %13, %14, %15, %16, %17, "           \
  "%18, %19, %20, %21, %22, %23, %24, %25, %26, %27, %28, %29, %30, %31, %32, %33, %34, %35, "  \
  "%36, %37, %38, %39, %40, %41, %42, %43, %44, %45, %46, %47, %48, %49, %50, %51, %52, %53, "  \
  "%54, %55, %56, %57, %58, %59, %60, %61, %62, %63, %64, %65, %66, %67, %68, %69, %70, %71}, "
template <int TA>
__device__ __forceinline__ void mma_tile(float (&d)[72], uint32_t da, uint32_t db, uint32_t keep) {
  asm volatile("{\n.reg .pred p;\n.reg .b64 da, db;\nsetp.ne.b32 p, %74, 0;\n"
    "mov.b64 da, {%72, %76};\nmov.b64 db, {%73, %76};\n"
    WGMMA "da, db, p, 1, 1, %75, 0;\nadd.s64 da, da, %77;\nadd.s64 db, db, 2;\n"
    WGMMA "da, db, 1, 1, 1, %75, 0;\nadd.s64 da, da, %77;\nadd.s64 db, db, 2;\n"
    WGMMA "da, db, 1, 1, 1, %75, 0;\nadd.s64 da, da, %77;\nadd.s64 db, db, 2;\n"
    WGMMA "da, db, 1, 1, 1, %75, 0;\n}\n"
    : "+f"(d[0]), "+f"(d[1]), "+f"(d[2]), "+f"(d[3]), "+f"(d[4]), "+f"(d[5]), "+f"(d[6]), "+f"(d[7]),
      "+f"(d[8]), "+f"(d[9]), "+f"(d[10]), "+f"(d[11]), "+f"(d[12]), "+f"(d[13]), "+f"(d[14]), "+f"(d[15]),
      "+f"(d[16]), "+f"(d[17]), "+f"(d[18]), "+f"(d[19]), "+f"(d[20]), "+f"(d[21]), "+f"(d[22]), "+f"(d[23]),
      "+f"(d[24]), "+f"(d[25]), "+f"(d[26]), "+f"(d[27]), "+f"(d[28]), "+f"(d[29]), "+f"(d[30]), "+f"(d[31]),
      "+f"(d[32]), "+f"(d[33]), "+f"(d[34]), "+f"(d[35]), "+f"(d[36]), "+f"(d[37]), "+f"(d[38]), "+f"(d[39]),
      "+f"(d[40]), "+f"(d[41]), "+f"(d[42]), "+f"(d[43]), "+f"(d[44]), "+f"(d[45]), "+f"(d[46]), "+f"(d[47]),
      "+f"(d[48]), "+f"(d[49]), "+f"(d[50]), "+f"(d[51]), "+f"(d[52]), "+f"(d[53]), "+f"(d[54]), "+f"(d[55]),
      "+f"(d[56]), "+f"(d[57]), "+f"(d[58]), "+f"(d[59]), "+f"(d[60]), "+f"(d[61]), "+f"(d[62]), "+f"(d[63]),
      "+f"(d[64]), "+f"(d[65]), "+f"(d[66]), "+f"(d[67]), "+f"(d[68]), "+f"(d[69]), "+f"(d[70]), "+f"(d[71])
    : "r"(da), "r"(db), "r"(keep), "n"(TA), "r"(0x40000040), "n"(TA ? 128 : 2));
}
__device__ __forceinline__ uint32_t desc_lo(uint32_t addr) { return ((addr & 0x3FFFF) >> 4) | 0x10000u; }

template <int N> struct Cursor {
  uint32_t slot = 0, ph = 0;
  __device__ __forceinline__ void next() { if (++slot == N) { slot = 0; ph ^= 1; } }
  __device__ __forceinline__ void skip(uint32_t k) { const uint32_t t = slot + k, q = t / N; slot = t - q * N; ph ^= q & 1; }
};

template <bool MAX> __device__ __forceinline__ float comb(float a, float b) { return MAX ? fmaxf(a, b) : a + b; }
template <bool MAX> __device__ __forceinline__ float xsplit(float lo, float hi, bool bit, int mask) {
  const float send = bit ? lo : hi, keep = bit ? hi : lo;
  return comb<MAX>(keep, __shfl_xor_sync(0xffffffffu, send, mask));
}
template <bool MAX> __device__ __forceinline__ void col_reduce(const float (&v)[36], float (&o)[5], int lane) {
  const bool b2 = lane & 16, b1 = lane & 8, b0 = lane & 4;
#pragma unroll
  for (int G = 0; G < 5; G++) {
    float a[4];
#pragma unroll
    for (int e = 0; e < 4; e++) a[e] = G < 4 ? xsplit<MAX>(v[8 * G + e], v[(8 * G + 4 + e) % 36], b2, 16) : v[8 * G + e];
    const float c0 = xsplit<MAX>(a[0], a[2], b1, 8), c1 = xsplit<MAX>(a[1], a[3], b1, 8);
    float r = xsplit<MAX>(c0, c1, b0, 4);
    if (G == 4) r = comb<MAX>(r, __shfl_xor_sync(0xffffffffu, r, 16));
    o[G] = r;
  }
}

struct Consumer {
  uint32_t a0, b0;
  uint32_t adj_a, adj_b;
  uint32_t a, b, aph = 0, bph = 0;
  uint32_t pa, pb, pend = 0;
  uint32_t lane0;

  __device__ __forceinline__ uint32_t da(uint32_t s) const { return s * (A_BYTES / 128) + adj_a; }
  __device__ __forceinline__ uint32_t db(uint32_t s) const { return s * (B_BYTES / 128) + adj_b; }
  __device__ __forceinline__ void next_a() { a += 8; if (a == a0 + NA * 8) { a = a0; aph ^= 1; } }
  __device__ __forceinline__ void next_b() { b += 8; if (b == b0 + NB * 8) { b = b0; bph ^= 1; } }
  __device__ __forceinline__ void rel(uint32_t sa, uint32_t sb_, uint32_t on) {
    mbar_arrive_if(sa + EA, lane0 & on);
    mbar_arrive_if(sb_ + EB, lane0 & on);
  }
  __device__ __forceinline__ void rel_pending() { rel(pa, pb, pend); pend = 0; }
  __device__ __forceinline__ void wait_ab() { mbar_wait2(a, aph, b, bph); }
  __device__ __forceinline__ void step(float (&acc)[72], uint32_t keep, uint32_t more) {
    const uint32_t sa = a, sb_ = b;
    wg_fence();
    mma_tile<1>(acc, da(sa), db(sb_), keep);
    wg_commit();
    next_a();
    next_b();
    asm volatile(
        "{\n.reg .pred p, q, m;\n.reg .u32 c;\n"
        "mbarrier.test_wait.parity.shared::cta.b64 p, [%0], %1;\n"
        "mbarrier.test_wait.parity.shared::cta.b64 q, [%2], %3;\n"
        "setp.ne.u32 m, %6, 0;\n"
        "wgmma.wait_group.sync.aligned 1;\n"
        "@m mbarrier.arrive.shared::cta.b64 _, [%4];\n"
        "@m mbarrier.arrive.shared::cta.b64 _, [%5];\n"
        "setp.eq.u32 m, %7, 0;\n"
        "and.pred p, p, q;\nor.pred p, p, m;\n@p bra WD;\n"
        "mov.u32 c, 0;\nWL:\n"
        "mbarrier.try_wait.parity.shared::cta.b64 p, [%0], %1;\n"
        "mbarrier.try_wait.parity.shared::cta.b64 q, [%2], %3;\n"
        "and.pred p, p, q;\n" SPIN_TAIL
        ::"r"(a), "r"(aph), "r"(b), "r"(bph), "r"(pa + EA), "r"(pb + EB), "r"(lane0 & pend), "r"(more) : "memory");
    pa = sa;
    pb = sb_;
    pend = 1;
  }
};

template <uint32_t V> struct Const { static constexpr uint32_t value = V; };

__global__ void __launch_bounds__(384, 1)
fused_mha_kernel(const __grid_constant__ Maps maps, const __grid_constant__ Ptrs ptrs, const int cta0, const int CS) {
  const int GB = CS == 8 ? 4 : 2;
  extern __shared__ __align__(1024) uint8_t smem_raw[];
  const uint32_t sb = __shfl_sync(0xffffffffu, (uint32_t)__cvta_generic_to_shared(smem_raw), 0);
  const int tid = threadIdx.x;
  const int warp = __shfl_sync(0xffffffffu, tid >> 5, 0);
  const int lane = tid & 31;
  asm volatile("griddepcontrol.launch_dependents;");
  int cta = cta0 + blockIdx.x;
  if (cta0 < 0) {
    const int k = blockIdx.x >> 1;
    int gpc = 0, row = k;
    if (k >= 36) { row = 4 + (k - 36) / 7; gpc = 1 + (k - 36) % 7; }
    else if (k >= 4) { gpc = (k - 4) & 7; row = ((k - 4) >> 3) + (gpc ? 0 : 4); }
    cta = (row & 4) * 16 + gpc * 8 + (row & 3) * 2 + (blockIdx.x & 1);
  }
  const int c = cta & 3, grp = cta >> 2, br = grp >> 4, b = grp & 15;
  const uint32_t rank = cta & (CS - 1);
  const int late = br;

  if (warp == 8) {
    if (lane < 9) bulk_prefetch(ptrs.x[br] + (size_t)(b * SQ + c * 36) * 1024 + lane * 4096, 4096);
  } else if (warp == 9) {
    const char* wq = ptrs.wq[br] + (size_t)(b * 32 + lane) * 8192 + c * 256;
    prefetch_l2(wq);
    prefetch_l2(wq + 128);
  } else if (warp == 10 && lane < 13) {
    asm volatile("prefetch.tensormap [%0];" ::"l"(&maps.x[0] + lane) : "memory");
  }
  if (lane == 0) {
#pragma unroll 1
    for (uint32_t a = BAR_FULLA + warp * 8; a < BAR_END; a += 96) {
      uint32_t cnt = 1;
      if (a >= BAR_EMPTYA && a < BAR_FULLB) cnt = 4;
      if ((a >= BAR_EMPTYB && a < BAR_PGATE) || a == BAR_QFULL) cnt = 8;
      if (a >= BAR_PEER && a < BAR_PEERA) cnt = GB - 1;
      mbar_init(sb + a, cnt);
    }
    if (warp == 0) {
      if (sb & 1023) asm volatile("trap;");
      sts32u(sb + OFF_BAD, 0);
    }
    asm volatile("fence.mbarrier_init.release.cluster;" ::: "memory");
  }
  asm volatile("barrier.cluster.arrive.relaxed.aligned;" ::: "memory");
  __syncthreads();

  if (warp >= 8) {
    asm volatile("setmaxnreg.dec.sync.aligned.u32 40;");
    const int rot = c & (4 - GB);
    if (warp < 10) {
      const int x = warp - 8;
      const uint32_t bar0 = sb + BAR_FULLA + x * NA * 8, dst0 = sb + OFF_A + x * NA * A_BYTES;
      Cursor<NA> cur;
      if (CS == 8) asm volatile("barrier.cluster.wait.aligned;" ::: "memory");
      uint64_t evict_first;
      asm volatile("createpolicy.fractional.L2::evict_first.b64 %0, 1.0;" : "=l"(evict_first));
      auto put_kv = [&](const CUtensorMap* m, int c0, int c1) {
        const uint32_t fb = bar0 + cur.slot * 8;
        mbar_wait(fb + EA, cur.ph ^ 1);
        tma_load_hint(dst0 + cur.slot * A_BYTES, m, c0, c1, fb, evict_first);
        cur.next();
      };
      uint32_t peer_ph = CS == 8 ? 0 : ~0u;
      const uint32_t wmask = CS == 8 ? 0x11u << c : 1u << rank;
      auto put_w = [&](const CUtensorMap* m, int c0, int c1, uint32_t kind) {
        const uint32_t fb = bar0 + cur.slot * 8;
        if (CS != 8 || kind == (rank >> 2)) {
          mbar_wait2(fb + EA, cur.ph ^ 1, fb + (BAR_PEERA - BAR_FULLA), (peer_ph >> cur.slot) & 1);
          tma_multicast2<A_BYTES>(dst0 + cur.slot * A_BYTES, m, c0, c1, fb, wmask);
          if (CS == 8) peer_ph ^= 1u << cur.slot;
        } else {
          mbar_wait(fb + EA, cur.ph ^ 1);
          relay_slot<A_BYTES>(fb, fb + (BAR_PEERA - BAR_FULLA), rank ^ 4);
        }
        cur.next();
      };
#pragma unroll 1
      for (int pass = 0; pass < 2; pass++) {
        int g = 0;
        auto put_wo = [&]() { put_w(&maps.wo[br], 128 * c + 64 * x, (g >> 3) * 512 + ((rot * 128 + g * 64) & 511), 1); g++; };
#pragma unroll 1
        for (int r = 0; r <= 8; r++) {
#pragma unroll 1
          for (int i = r < 8 ? 0 : 8; i < 8; i++) put_w(&maps.wq[br], (4 * r + c) * 128 + 64 * x, 64 * i, 0);
#pragma unroll 1
          for (int i = r < 8 ? (r >= R1 ? 4 + 2 * x : 0) : 16; i > 0; i--) put_wo();
          if (r == 8) break;
          if (late && r + pass == 0) {
            mbar_wait(sb + BAR_QFULL, 0);
            wait_until(clock32() + STAGGER);
          }
          const int kv = (b * 32 + 4 * r + c) * 512;
          int vrow = kv;
#pragma unroll 1
          for (int j = 0; j < 4; j++) {
#pragma unroll 1
            for (int h = 0; h < 2; h++) put_kv(&maps.k[br], 64 * h, kv + 64 * (2 * j + x));
            if (j + x < 2) {
#pragma unroll 1
              for (int h = r >= R1 ? 2 : 0; h > 0; h--) put_wo();
            } else {
#pragma unroll 1
              for (int h = j < 3 ? 2 : 6 - 2 * x; h > 0; h--, vrow += 64) put_kv(&maps.v[br], 64 * x, vrow);
            }
          }
        }
        if (pass) break;
        mbar_wait(sb + BAR_REDO, 0);
        if (!lds_uniform(sb + OFF_REDO)) break;
      }
    } else if (warp == 10) {
      asm volatile("barrier.cluster.wait.aligned;" ::: "memory");
      const uint32_t me = rank & (GB - 1), bmask = ((1u << GB) - 1) << (rank - me);
      const uint32_t base = (uint32_t)*(volatile unsigned long long*)&g_flag[cta * 16];
      const unsigned long long* const fp = &g_flag[(grp * 4 + (lane & 3)) * 16];
      Cursor<NB> cur;
      uint32_t gate = NB, gph = 1;
      uint32_t peer_ph = 0;
      uint32_t pubs = 0, sels = 0;
      auto need = [&](uint32_t hh, uint32_t rounds) {
        for (int spin = 0; ((pubs >> (8 * hh)) & 255) < 2 * rounds; spin++) {
          if (spin > (1 << 23)) asm volatile("trap;");
          unsigned long long fv;
          asm volatile("ld.acquire.gpu.global.u64 %0, [%1];" : "=l"(fv) : "l"(fp) : "memory");
          pubs = __reduce_or_sync(0xffffffffu, (((uint32_t)fv - base) & 255) << (8 * (lane & 3)));
          sels = __reduce_or_sync(0xffffffffu, ((uint32_t)(fv >> 32) & 255) << (8 * (lane & 3)));
          __syncwarp();
          fence_async_global();
        }
      };
      auto mine = [&](uint32_t loader) {
        if (gate < NB) mbar_wait(sb + BAR_PGATE + 8 * gate, gph);
        gate++;
        const uint32_t fb = sb + BAR_FULLB + cur.slot * 8;
        if (loader != me) {
          mbar_wait(fb + EB, cur.ph ^ 1);
          relay_slot<B_BYTES>(fb, fb + (BAR_PEER - BAR_FULLB), rank - me + loader);
          return false;
        }
        mbar_wait2(fb + EB, cur.ph ^ 1, fb + (BAR_PEER - BAR_FULLB), (peer_ph >> cur.slot) & 1);
        peer_ph ^= 1u << cur.slot;
        return true;
      };
#pragma unroll 1
      for (int pass = 0; pass < 2; pass++) {
        uint32_t g = 0;
#pragma unroll 1
        for (int r = 0; r <= 8; r++) {
#pragma unroll 1
          for (int i = r < 8 ? 0 : 8; i < 8; i++) {
            if (mine(0)) tma_multicast2<B_BYTES>(sb + OFF_B + cur.slot * B_BYTES, &maps.x[br], 64 * i, b * SQ, sb + BAR_FULLB + cur.slot * 8, bmask);
            cur.next();
          }
#pragma unroll 1
          for (int i = r < 8 ? (r >= R1 ? 8 : 0) : 16; i > 0; i--, g++) {
            const uint32_t hh = (rot + (g >> 1)) & 3, w = ((g >> 2) & 2) + (g & 1);
            if (me == 1) need(hh, pass * 8 + (g >> 3) + 1);
            const int c1 = ((sels >> (8 * hh + w)) & 1) * 64, c2 = ((grp * 4 + hh) * NWIN + w) * 4;
            if (mine(1)) tma_multicast3(sb + OFF_B + cur.slot * B_BYTES, &maps.o, c1, c2, sb + BAR_FULLB + cur.slot * 8, bmask);
            cur.next();
          }
          if (r + pass == 0) {
            char* const scr = ptrs.scr + (size_t)cta * NWIN * 65536;
            uint32_t v, sel = 0;
            if (lane < 2 * NWIN) {
              asm volatile("atom.relaxed.gpu.global.exch.b32 %0, [%1], 0;" : "=r"(v) : "l"(scr + (lane >> 1) * 65536 + 53248 + (lane & 1) * 8192) : "memory");
              sel = v == 0xffffffffu;
            }
            sel = __reduce_and_sync(0xffffffffu, sel);
            if (lane == 0) {
#pragma unroll 1
              for (int w = 0; w < NWIN; w++) sel |= nearer_placement(scr + w * 65536) << w;
              sts32u(sb + OFF_SEL, sel);
            }
            mbar_arrive_if(sb + BAR_SEL, lane == 0);
            __syncwarp();
          }
          if (r < 8) {
            cur.skip(8);
            gate = 0;
            gph ^= 1;
            if (me == 1) {
              mbar_wait(sb + BAR_PGATE, gph);
#pragma unroll 1
              for (uint32_t hh = 0; hh < 4; hh++) need(hh, pass * 8 + r);
            }
          }
        }
        if (pass) break;
        mbar_wait(sb + BAR_REDO, 0);
        if (!lds_uniform(sb + OFF_REDO)) break;
      }
    } else {
      const uint32_t base = (uint32_t)*(volatile unsigned long long*)&g_flag[cta * 16];
      auto watch = [&](uint32_t off, uint32_t least, int n) {
        const char* fp = (const char*)&g_flag[((cta & -n) + (lane & (n - 1))) * 16] + off;
        uint32_t v;
        for (int spin = 0;; spin++) {
          asm volatile("ld.acquire.gpu.global.u32 %0, [%1];" : "=r"(v) : "l"(fp) : "memory");
          if (__all_sync(0xffffffffu, (int)(v - base - least) >= 0)) break;
          if (spin > (1 << 23)) asm volatile("trap;");
        }
        return v - base;
      };
      {
        uint32_t t = clock32() + late * PF_LATE;
#pragma unroll 1
        for (int q = 0; q < 16; q++, t += PF_STEP) {
          wait_until(t);
          const int e = (int)(0xFEDC76BA54983210ull >> (4 * q)) & 15;
          if (lane == 0) bulk_prefetch((e & 8 ? ptrs.v[br] : ptrs.k[br]) + (size_t)(b * 32 + c) * 131072 + (e & 7) * 16384, 16384);
          __syncwarp();
        }
      }
      Cursor<NB> cur;
      uint32_t redo = 0, sel = 0;
#pragma unroll 1
      for (int pass = 0; pass < 2; pass++) {
        uint32_t bad = 0;
#pragma unroll 1
        for (int p = pass ? lane : SQ; p < SQ; p += 32) sts32(sb + OFF_LSUM + p * 4, 0.f);
        __syncwarp();
#pragma unroll 1
        for (int r = 0; r <= 8; r++) {
          const int R = pass * 8 + r;
          cur.skip(r >= R1 ? 16 : 8);
          if (r < 8) {
#pragma unroll 1
            for (int t = 0; t < 8; t++) {
              bar_sync<160>(NB_PSTG + (t & 3));
              fence_async_smem();
              mbar_arrive_if(sb + BAR_FULLB + cur.slot * 8, lane == 0);
              mbar_arrive_if(sb + BAR_PGATE + (t - (8 - NB)) * 8, lane == 0 && t >= 8 - NB);
              if (lane == 0 && t == NB - 1)
                asm volatile("st.relaxed.gpu.global.u32 [%0+8], %1;" ::"l"(&g_flag[cta * 16]), "r"(base + R + 1) : "memory");
              cur.next();
            }
            __syncwarp();
            bar_sync<288>(NB_LFULL);
            if (pass) {
#pragma unroll 1
              for (int p = lane; p < SQ; p += 32) {
                sts32(sb + OFF_LINV + p * 4, rcp(lds32(sb + OFF_LSUM + p * 4)));
                sts32(sb + OFF_LSUM + p * 4, 0.f);
              }
            } else if (lane < 24) {
              const uint32_t o = sb + OFF_LPART + lane * 8;
              float2 v[3][4], a[3];
#pragma unroll
              for (int h = 0; h < 3; h++)
#pragma unroll
                for (int q = 0; q < 4; q++) v[h][q] = lds64(o + h * 192 + q * 576);
#pragma unroll
              for (int h = 0; h < 3; h++)
                a[h] = make_float2((v[h][0].x + v[h][1].x) + (v[h][2].x + v[h][3].x), (v[h][0].y + v[h][1].y) + (v[h][2].y + v[h][3].y));
#pragma unroll
              for (int h = 0; h < 3; h++)
#pragma unroll
                for (int q = 0; q < 4; q++) v[h][q] = lds64(o + h * 192 + (q + 4) * 576);
#pragma unroll
              for (int h = 0; h < 3; h++) {
                const float l0 = a[h].x + ((v[h][0].x + v[h][1].x) + (v[h][2].x + v[h][3].x));
                const float l1 = a[h].y + ((v[h][0].y + v[h][1].y) + (v[h][2].y + v[h][3].y));
                bad |= !(l0 >= 1.f && l0 <= L_MAX && l1 >= 1.f && l1 <= L_MAX);
                asm volatile("st.shared.v2.f32 [%0], {%1, %2};" ::"r"(o + h * 192), "f"(rcp(l0)), "f"(rcp(l1)) : "memory");
              }
            }
            bad = __any_sync(0xffffffffu, bad);
            mbar_arrive_if(sb + BAR_LREADY, lane == 0);
            watch(8, R + 1, 4);
            if (R == 0) {
              mbar_wait(sb + BAR_SEL, 0);
              sel = lds_uniform(sb + OFF_SEL);
            }
          }
#pragma unroll 1
          for (int h = 0; h < 2; h++) {
            if (r >= 7) bar_sync<160>(NB_OSTG + 1);
            bar_sync<160>(NB_OSTG + h);
            fence_async_smem();
            const uint32_t w = 2 * (r & 1) + h;
            if (r == 8) {
              tma_store2(&maps.out, br * 512 + c * 128, b * SQ, sb + OFF_Q);
              tma_store2(&maps.out, br * 512 + c * 128 + 64, b * SQ, sb + OFF_Q + B_BYTES);
            } else if (r == 7) {
              tma_store3(&maps.o, ((sel >> w) & 1) * 64, (cta * NWIN + w) * 4, sb + OFF_Q);
              tma_store3(&maps.o, ((sel >> (w + 1)) & 1) * 64, (cta * NWIN + w + 1) * 4, sb + OFF_Q + B_BYTES);
            } else {
#pragma unroll 1
              for (int z = 0; z < 3; z++) {
                tma_store3(&maps.o1, ((sel >> w) & 1) * 64, (cta * NWIN + w) * 4 + z, sb + OFF_Q + h * B_BYTES + z * 6144);
                if (z < 2) __nanosleep(150);
              }
            }
            asm volatile("cp.async.bulk.commit_group;" ::: "memory");
            bad |= lds32u(sb + OFF_BAD);
            asm volatile("cp.async.bulk.wait_group 0;" ::: "memory");
            __syncwarp();
            mbar_arrive_if(sb + BAR_QFREE + (h + lane) * 8, lane == 0 || (lane == 1 && r >= 7));
            if (r >= 7) break;
          }
          if (r < 8) {
            if (lane == 0) {
              const unsigned long long f = ((unsigned long long)sel << 32) | (base + 2 * (R + 1) + (pass ? 0 : bad));
              asm volatile("st.release.gpu.global.u64 [%0], %1;" ::"l"(&g_flag[cta * 16]), "l"(f) : "memory");
            }
            __syncwarp();
            if (R == 7) {
              redo = __any_sync(0xffffffffu, watch(0, 16, 8) != 16);
              if (lane == 0) sts32u(sb + OFF_REDO, redo);
              mbar_arrive_if(sb + BAR_REDO, lane == 0);
            }
          }
        }
        if (!redo) break;
      }
    }
  } else {
    asm volatile("setmaxnreg.inc.sync.aligned.u32 232;");
    const uint32_t x = warp >> 2;
    Consumer cs;
    cs.a = cs.a0 = cs.pa = sb + BAR_FULLA + x * NA * 8;
    cs.b = cs.b0 = cs.pb = sb + BAR_FULLB;
    cs.adj_a = desc_lo(sb + OFF_A + x * NA * A_BYTES) - cs.a0 * (A_BYTES / 128);
    cs.adj_b = __shfl_sync(0xffffffffu, desc_lo(sb + OFF_B) - cs.b0 * (B_BYTES / 128), 0);
    cs.lane0 = lane == 0;
    const uint32_t qdesc = __shfl_sync(0xffffffffu, desc_lo(sb + OFF_Q), 0);
    const uint32_t st_off = __shfl_sync(
        0xffffffffu, ((lane >> 4) * 8 + (lane & 7)) * 128 + (((2 * (warp & 3) + ((lane >> 3) & 1)) ^ (lane & 7)) << 4), lane);
    const uint32_t v_off = (lane & 3) * 16;
    const uint32_t r_off = (16 * (lane >> 4) + 4 * (lane & 3) + ((lane >> 2) & 3)) * 4;

    auto run = [&](auto pass_c) {
      constexpr uint32_t pass = decltype(pass_c)::value;
      float4* const accp = g_acc + (size_t)cta * 18 * 256 + threadIdx.x;
      float accA[72], accB[72];
      float l[36];
      uint32_t lp[18];
      uint32_t o16[36];
      float osc = 1.f;
#pragma unroll
      for (int i = 0; i < 72; i++) { accA[i] = 0.f; accB[i] = 0.f; }
#pragma unroll
      for (int i = 0; i < 36; i++) { l[i] = 0.f; lp[i / 2] = 0; o16[i] = 0; }
      Cursor<NB> pw;
      uint32_t kready = 0, vready = 0;

      auto rescale = [&](int t) {
        if (pass && t > 0) {
          wg_wait<0>();
          pin(accB);
#pragma unroll
          for (int jj = 0; jj < 9; jj++) {
            const int i = 8 * jj;
            const float4 f = lds128(sb + OFF_FAC + (t & 3) * 576 + v_off + jj * 64);
            accB[i] *= f.x; accB[i + 1] *= f.y; accB[i + 2] *= f.x; accB[i + 3] *= f.y;
            accB[i + 4] *= f.z; accB[i + 5] *= f.w; accB[i + 6] *= f.z; accB[i + 7] *= f.w;
          }
        }
      };

#pragma unroll 1
      for (int r = -1, n = 0, t = 8;; t += 2) {
        if (t >= 8) {
          t = x;
          r++;
          n = r >= R1 && r < 8;
          cs.wait_ab();
          if (r > 0) {
            const int tl = pass ? 7 : 6 + x;
#pragma unroll 1
            for (int u = 4 + 2 * x; u < 8; u++) {
              rescale(u);
              cs.step(accB, 1, u != tl);
              if (u == tl) {
                float l5[5];
                if (!pass) {
#pragma unroll
                  for (int i = 0; i < 18; i++) { l[2 * i] = __uint_as_float(lp[i] << 16); l[2 * i + 1] = __uint_as_float(lp[i] & 0xffff0000u); }
                }
                col_reduce<false>(l, l5, lane);
#pragma unroll
                for (int G = 0; G < 5; G++) {
                  const uint32_t o = G < 4 ? r_off + G * 128 : (r_off & 63) + 512;
                  if (pass) {
                    if (x == 0) l5[G] *= lds32(sb + OFF_FAC + 3 * 576 + o);
                    if (G < 4 || lane < 16) asm volatile("red.shared.add.f32 [%0], %1;" ::"r"(sb + OFF_LSUM + o), "f"(l5[G]) : "memory");
                  } else if (G < 4 || lane < 16) {
                    sts32(sb + OFF_LPART + warp * 576 + o, l5[G]);
                  }
                }
                bar_arrive<288>(NB_LFULL);
                cs.wait_ab();
              }
            }
          }
          if (r == 8) {
            wg_wait<0>();
            if (pass) {
#pragma unroll
              for (int i = 0; i < 18; i++) {
                const float4 v = __ldcg(accp + i * 256);
                accA[4 * i] = v.x; accA[4 * i + 1] = v.y; accA[4 * i + 2] = v.z; accA[4 * i + 3] = v.w;
              }
            } else {
              const float inv = rcp(osc);
#pragma unroll
              for (int i = 0; i < 36; i++) {
                const float2 v = __half22float2(*reinterpret_cast<const __half2*>(&o16[i]));
                accA[2 * i] = v.x * inv; accA[2 * i + 1] = v.y * inv;
              }
            }
          } else {
            cs.step(accA, 0, 1);
          }
          const int nq = r < 8 ? 8 : 16;
          const int ko = r == 0 ? -1 : (r == 8 ? (x ? FB : FA) : (x ? KB : KA));
#pragma unroll 1
          for (int i = r < 8; i < nq; i++) {
            cs.step(accA, 1, i != ko && (i + 1 < nq || n));
            if (i == ko) {
              mbar_wait(sb + BAR_LREADY, (r - 1) & 1);
              pin(accB);
#pragma unroll
              for (int jj = 0; jj < 9; jj++) {
                const float4 f = lds128(sb + OFF_LINV + v_off + jj * 64);
                l[4 * jj] = f.x; l[4 * jj + 1] = f.y; l[4 * jj + 2] = f.z; l[4 * jj + 3] = f.w;
              }
              uint32_t chk = 0;
#pragma unroll
              for (int jj = 0; jj < 9; jj++) {
                const int q = 8 * jj, f = 4 * jj;
                const uint32_t r0 = pack_bf16(accB[q] * l[f], accB[q + 1] * l[f + 1]), r1 = pack_bf16(accB[q + 2] * l[f], accB[q + 3] * l[f + 1]);
                const uint32_t r2 = pack_bf16(accB[q + 4] * l[f + 2], accB[q + 5] * l[f + 3]), r3 = pack_bf16(accB[q + 6] * l[f + 2], accB[q + 7] * l[f + 3]);
                stsm_t(sb + OFF_Q + x * B_BYTES + st_off + jj * 2048, r0, r1, r2, r3);
                asm("fma.rn.bf16x2 %0, %1, %2, %0;" : "+r"(chk) : "r"(r0), "r"(r1));
                asm("fma.rn.bf16x2 %0, %1, %2, %0;" : "+r"(chk) : "r"(r2), "r"(r3));
                if (jj == 2) {
                  wg_wait<0>();
                  cs.rel_pending();
                }
              }
              if ((chk & 0x7F80u) == 0x7F80u || (chk & 0x7F800000u) == 0x7F800000u) sts32u(sb + OFF_BAD, 1);
              bar_arrive<160>(NB_OSTG + x);
              cs.wait_ab();
            }
          }
          pw.slot = (cs.b - cs.b0) >> 3;
          pw.ph = cs.bph;
          pw.skip(8 * n + x);
          const int n1 = n ? 4 + 2 * x : 1, kq = n ? 2 * x : 0;
#pragma unroll 1
          for (int i = 0; i < n1; i++) {
            if (n) {
              cs.step(accB, i > 0, i != kq && i + 1 < n1);
            } else {
              wg_wait<0>();
              cs.rel_pending();
            }
            if (i == kq) {
              if (r + pass > 0) mbar_wait(sb + BAR_QFREE + x * 8, (pass + r - 1) & 1);
              pin(accA);
              const float qs = (pass || r == 8) ? 1.f : SCL;
#pragma unroll
              for (int jj = 0; jj < 9; jj++) {
                const int q = 8 * jj;
                stsm_t(sb + OFF_Q + x * B_BYTES + st_off + jj * 2048, pack_bf16(accA[q] * qs, accA[q + 1] * qs),
                       pack_bf16(accA[q + 2] * qs, accA[q + 3] * qs), pack_bf16(accA[q + 4] * qs, accA[q + 5] * qs),
                       pack_bf16(accA[q + 6] * qs, accA[q + 7] * qs));
              }
              if (r == 8) {
                bar_arrive<160>(NB_OSTG + x);
              } else {
                fence_async_smem();
                __syncwarp();
                mbar_arrive_if(sb + BAR_QFULL, cs.lane0);
              }
              if (n) cs.wait_ab();
            }
          }
#pragma unroll
          for (int i = 0; i < 36; i++) { l[i] = 0.f; lp[i / 2] = 0; }
          if (r == 8) {
            wg_wait<0>();
            break;
          }
          mbar_wait(sb + BAR_QFULL, r & 1);
          kready = vready = 0;
          if (x) bar_sync<256>(3);
        }
        const uint32_t k0 = cs.a, k0ph = cs.aph;
        cs.next_a();
        const uint32_t k1 = cs.a;
        if (!kready) mbar_wait2(k0, k0ph, k1, cs.aph);
        cs.next_a();
        wg_fence();
        mma_tile<0>(accA, cs.da(k0), qdesc, 0);
        mma_tile<0>(accA, cs.da(k1), qdesc + (B_BYTES >> 4), 1);
        wg_commit();
        const int tp = t + (int)x - 4;
        if (tp == 0 && n) {
          wg_wait<1>();
          pin(accB);
          if (pass) {
            if (r == R1) {
#pragma unroll
              for (int i = 0; i < 18; i++) accp[i * 256] = make_float4(accB[4 * i], accB[4 * i + 1], accB[4 * i + 2], accB[4 * i + 3]);
            } else {
#pragma unroll
              for (int i = 0; i < 18; i++)
                asm volatile("red.global.add.v4.f32 [%0], {%1, %2, %3, %4};" ::"l"(accp + i * 256), "f"(accB[4 * i]),
                             "f"(accB[4 * i + 1]), "f"(accB[4 * i + 2]), "f"(accB[4 * i + 3]) : "memory");
            }
          } else {
            if (r == R1) {
              float m = 0.f;
#pragma unroll
              for (int i = 0; i < 72; i++) m = fmaxf(m, fabsf(accB[i]));
              const uint32_t e = min(max(__float_as_uint(m) >> 23, 20u), 240u);
              osc = __uint_as_float((258u - e) << 23);
            }
#pragma unroll
            for (int i = 0; i < 36; i++) {
              uint32_t h;
              asm("cvt.rn.f16x2.f32 %0, %1, %2;" : "=r"(h) : "f"(accB[2 * i + 1] * osc), "f"(accB[2 * i] * osc));
              asm("add.rn.f16x2 %0, %0, %1;" : "+r"(o16[i]) : "r"(h));
            }
            if (r == 7) {
              uint32_t chk = 0;
#pragma unroll
              for (int i = 0; i < 36; i++) asm("fma.rn.f16x2 %0, %1, %2, %0;" : "+r"(chk) : "r"(o16[i]), "r"(0u));
              if (chk & 0x7C007C00u) sts32u(sb + OFF_BAD, 1);
            }
          }
        }
        const uint32_t trail = tp >= 0 || n;
        const uint32_t va = cs.a, pa = cs.b;
        uint32_t vb = va, pb = pa;
        if (trail) {
          if (!vready) cs.wait_ab();
          cs.next_a();
          cs.next_b();
          vb = cs.a;
          pb = cs.b;
          rescale(tp);
          wg_fence();
          mma_tile<1>(accB, cs.da(va), cs.db(pa), tp != 0);
          wg_commit();
          wg_wait<2>();
          cs.rel_pending();
          mbar_wait3(vb, cs.aph, pb, cs.bph, sb + BAR_EMPTYB + pw.slot * 8, pw.ph ^ 1);
          cs.next_a();
          cs.next_b();
          rescale(tp + 1);
          wg_fence();
          mma_tile<1>(accB, cs.da(vb), cs.db(pb), 1);
          wg_commit();
          if (t == 0) bar_arrive<256>(3);
          wg_wait<2>();
        } else {
          if (t == 0) bar_arrive<256>(3);
          mbar_wait(sb + BAR_EMPTYB + pw.slot * 8, pw.ph ^ 1);
          wg_wait<0>();
        }
        pin(accA);
        const uint32_t ptile = sb + OFF_B + pw.slot * B_BYTES + st_off;
        mbar_arrive_if(k0 + EA, cs.lane0);
        mbar_arrive_if(k1 + EA, cs.lane0);

        if (pass) {
          const uint32_t mo = sb + OFF_M + ((t + 1) & 1) * 576, mn = sb + OFF_M + (t & 1) * 576;
          const uint32_t wt = tid & 127;
          float lm[36], m5[5];
#pragma unroll
          for (int i = 0; i < 18; i++) {
            lm[2 * i] = fmaxf(accA[4 * i], accA[4 * i + 2]);
            lm[2 * i + 1] = fmaxf(accA[4 * i + 1], accA[4 * i + 3]);
          }
          col_reduce<true>(lm, m5, lane);
          if (t > 0) {
            const uint32_t ps = pw.slot == 0 ? NB - 1 : pw.slot - 1;
            mbar_wait(sb + BAR_FULLB + ps * 8, pw.slot == 0 ? pw.ph ^ 1 : pw.ph);
          }
          sts32(mn + wt * 4, M_INIT);
          if (wt < 16) sts32(mn + 512 + wt * 4, M_INIT);
          bar_sync<128>(1 + x);
#pragma unroll
          for (int G = 0; G < 5; G++) {
            const uint32_t o = G < 4 ? r_off + G * 128 : (r_off & 63) + 512;
            float v = m5[G] * SCL;
            if (t > 0) v = fmaxf(v, lds32(mo + o));
            if (v >= 0.f) asm volatile("red.shared.max.s32 [%0], %1;" ::"r"(mn + o), "r"(__float_as_int(v)) : "memory");
            else asm volatile("red.shared.min.u32 [%0], %1;" ::"r"(mn + o), "r"(__float_as_uint(v)) : "memory");
          }
          bar_sync<128>(1 + x);
          if (t > 0) {
            const uint32_t f = sb + OFF_FAC + (t & 3) * 576;
            sts32(f + wt * 4, ex2(lds32(mo + wt * 4) - lds32(mn + wt * 4)));
            if (wt < 16) sts32(f + 512 + wt * 4, ex2(lds32(mo + 512 + wt * 4) - lds32(mn + 512 + wt * 4)));
            bar_sync<128>(1 + x);
          }
#pragma unroll
          for (int jj = 0; jj < 9; jj++) {
            const int i = 8 * jj;
            if (t > 1) {
              const float4 f0 = lds128(sb + OFF_FAC + ((t - 1) & 3) * 576 + v_off + jj * 64);
              const float4 f1 = lds128(sb + OFF_FAC + (t & 3) * 576 + v_off + jj * 64);
              l[4 * jj] *= f0.x * f1.x; l[4 * jj + 1] *= f0.y * f1.y; l[4 * jj + 2] *= f0.z * f1.z; l[4 * jj + 3] *= f0.w * f1.w;
            }
            const float4 m = lds128(mn + v_off + jj * 64);
            const float p0 = ex2(fmaf(accA[i], SCL, -m.x)), p1 = ex2(fmaf(accA[i + 1], SCL, -m.y));
            const float p2 = ex2(fmaf(accA[i + 2], SCL, -m.x)), p3 = ex2(fmaf(accA[i + 3], SCL, -m.y));
            const float p4 = ex2(fmaf(accA[i + 4], SCL, -m.z)), p5 = ex2(fmaf(accA[i + 5], SCL, -m.w));
            const float p6 = ex2(fmaf(accA[i + 6], SCL, -m.z)), p7 = ex2(fmaf(accA[i + 7], SCL, -m.w));
            stsm_t(ptile + jj * 2048, pack_bf16(p0, p1), pack_bf16(p2, p3), pack_bf16(p4, p5), pack_bf16(p6, p7));
            l[4 * jj] += p0 + p2; l[4 * jj + 1] += p1 + p3; l[4 * jj + 2] += p4 + p6; l[4 * jj + 3] += p5 + p7;
          }
          wg_wait<0>();
          cs.rel(va, pa, trail);
          cs.rel(vb, pb, trail);
        } else {
#pragma unroll
          for (int jj = 0; jj < 9; jj++) {
            const int i = 8 * jj;
            const uint32_t r0 = pack_bf16(ex2(accA[i]), ex2(accA[i + 1])), r1 = pack_bf16(ex2(accA[i + 2]), ex2(accA[i + 3]));
            const uint32_t r2 = pack_bf16(ex2(accA[i + 4]), ex2(accA[i + 5])), r3 = pack_bf16(ex2(accA[i + 6]), ex2(accA[i + 7]));
            stsm_t(ptile + jj * 2048, r0, r1, r2, r3);
            lp[2 * jj] = add_bf16x2(lp[2 * jj], add_bf16x2(r0, r1));
            lp[2 * jj + 1] = add_bf16x2(lp[2 * jj + 1], add_bf16x2(r2, r3));
            if (jj == 3) {
              wg_wait<1>();
              cs.rel(va, pa, trail);
            }
            if (jj == 5) {
              wg_wait<0>();
              cs.rel(vb, pb, trail);
            }
            if (jj == 6) {
              Consumer nx = cs;
              kready = mbar_test(nx.a, nx.aph);
              nx.next_a();
              kready &= mbar_test(nx.a, nx.aph);
              nx.next_a();
              vready = mbar_test(nx.a, nx.aph) & mbar_test(nx.b, nx.bph);
            }
          }
        }
        bar_arrive<160>(NB_PSTG + (t & 3));
        pw.skip(2);
      }
    };
    run(Const<0>());
    mbar_wait(sb + BAR_REDO, 0);
    if (lds_uniform(sb + OFF_REDO)) run(Const<1>());
  }
}

typedef CUresult (*EncodeFn)(CUtensorMap*, CUtensorMapDataType, cuuint32_t, void*, const cuuint64_t*, const cuuint64_t*,
                             const cuuint32_t*, const cuuint32_t*, CUtensorMapInterleave, CUtensorMapSwizzle,
                             CUtensorMapL2promotion, CUtensorMapFloatOOBfill);

void encode(EncodeFn enc, CUtensorMap* m, int rank, const void* base, const cuuint64_t* dims, const cuuint64_t* strides, const cuuint32_t* box) {
  const cuuint32_t es[3] = {1, 1, 1};
  enc(m, CU_TENSOR_MAP_DATA_TYPE_BFLOAT16, rank, const_cast<void*>(base), dims, strides, box, es, CU_TENSOR_MAP_INTERLEAVE_NONE,
      CU_TENSOR_MAP_SWIZZLE_128B, CU_TENSOR_MAP_L2_PROMOTION_L2_128B, CU_TENSOR_MAP_FLOAT_OOB_FILL_NONE);
}
void encode_2d(EncodeFn enc, CUtensorMap* m, const void* base, uint64_t cols, uint64_t rows, uint32_t box_rows) {
  const cuuint64_t dims[2] = {cols, rows}, strides[1] = {cols * 2};
  const cuuint32_t box[2] = {64, box_rows};
  encode(enc, m, 2, base, dims, strides, box);
}

}

extern "C" void kernel_launch(void* const* d_in, const int* in_sizes, int n_in, void* d_out, int out_size) {
  (void)in_sizes; (void)n_in; (void)out_size;
  void* fn = nullptr;
  cudaDriverEntryPointQueryResult st;
  cudaGetDriverEntryPoint("cuTensorMapEncodeTiled", &fn, cudaEnableDefault, &st);
  EncodeFn enc = (EncodeFn)fn;
  void* scr = nullptr;
  cudaGetSymbolAddress(&scr, g_scr);
  Maps maps;
  Ptrs ptrs;
  ptrs.scr = (char*)(((uintptr_t)scr + 65535) & ~(uintptr_t)65535);
  for (int br = 0; br < 2; br++) {
    encode_2d(enc, &maps.x[br], d_in[5 * br + 0], 512, 16 * SQ, SQ);
    encode_2d(enc, &maps.k[br], d_in[5 * br + 1], 128, 16 * 32 * 512, 64);
    encode_2d(enc, &maps.v[br], d_in[5 * br + 2], 128, 16 * 32 * 512, 64);
    encode_2d(enc, &maps.wq[br], d_in[5 * br + 3], 4096, 512, 64);
    encode_2d(enc, &maps.wo[br], d_in[5 * br + 4], 512, 4096, 64);
    ptrs.x[br] = (const char*)d_in[5 * br + 0];
    ptrs.k[br] = (const char*)d_in[5 * br + 1];
    ptrs.v[br] = (const char*)d_in[5 * br + 2];
    ptrs.wq[br] = (const char*)d_in[5 * br + 3];
  }
  {
    const cuuint64_t dims[3] = {64, 128, (cuuint64_t)128 * NWIN * 4 - 1}, strides[2] = {128, 16384};
    const cuuint32_t box3[3] = {64, 48, 3}, box1[3] = {64, 48, 1};
    encode(enc, &maps.o, 3, ptrs.scr + 4096, dims, strides, box3);
    encode(enc, &maps.o1, 3, ptrs.scr + 4096, dims, strides, box1);
  }
  encode_2d(enc, &maps.out, d_out, 1024, 16 * SQ, SQ);
  cudaFuncSetAttribute(fused_mha_kernel, cudaFuncAttributeMaxDynamicSharedMemorySize, SMEM_BYTES);
  cudaLaunchConfig_t cfg = {};
  cfg.blockDim = dim3(384);
  cfg.dynamicSmemBytes = SMEM_BYTES;
  cfg.stream = cudaStreamPerThread;
  cudaLaunchAttribute at[2];
  at[0].id = cudaLaunchAttributeClusterDimension;
  at[0].val.clusterDim.x = 8;
  at[0].val.clusterDim.y = 1;
  at[0].val.clusterDim.z = 1;
  at[1].id = cudaLaunchAttributeProgrammaticStreamSerialization;
  at[1].val.programmaticStreamSerializationAllowed = 1;
  cfg.attrs = at;
  cfg.numAttrs = 1;
  cfg.gridDim = dim3(120);
  int fit = 0;
  cudaOccupancyMaxActiveClusters(&fit, fused_mha_kernel, &cfg);
  if (fit >= 15) {
    cudaLaunchKernelEx(&cfg, fused_mha_kernel, maps, ptrs, 0, 8);
    at[0].val.clusterDim.x = 2;
    cfg.numAttrs = 2;
    cfg.gridDim = dim3(8);
    cudaLaunchKernelEx(&cfg, fused_mha_kernel, maps, ptrs, 120, 2);
  } else {
    at[0].val.clusterDim.x = 2;
    cfg.gridDim = dim3(128);
    cudaLaunchKernelEx(&cfg, fused_mha_kernel, maps, ptrs, -1, 2);
  }
}
```
